```python
import torch

def _softmax(x, axis=-1):
    return torch.softmax(x, dim=axis)
def _gelu(x):
    return torch.nn.functional.gelu(x, approximate="tanh")
def _silu(x):
    return torch.nn.functional.silu(x)
def _sigmoid(x):
    return torch.sigmoid(x)
def _layernorm(x, axis=-1, eps=1e-5):
    m = x.mean(dim=axis, keepdim=True)
    v = x.var(dim=axis, keepdim=True, unbiased=False)
    return (x - m) / torch.sqrt(v + eps)
def _scatter_add(tgt, idx, src, axis=0):
    return tgt.clone().index_add_(axis, idx, src)
def _segment_sum(src, seg, n):
    out = torch.zeros((n,) + src.shape[1:], dtype=src.dtype)
    return out.index_add_(0, seg, src)
def _pad(x, pw):
    flat = tuple(v for pair in reversed(pw) for v in pair)
    return torch.nn.functional.pad(x, flat)

kernel_name = 'parallel_sum__linear_attn_block__dense_activation_mish__prompt'

def setup_inputs():

    _w = (lambda a: (lambda t: t.to(torch.bfloat16) if t.is_floating_point() else t)(torch.as_tensor(a)))
    def _A_setup():
        B, S, D = 1, 2048, 512
        return {
            "x": _w((lambda *s: torch.randn(*s, dtype=torch.bfloat16) * 0.05)(B, S, D)),
            "wqkv": _w((lambda *s: torch.randn(*s, dtype=torch.bfloat16) * 0.1)(D, 3 * D)),
            "wo": _w((lambda *s: torch.randn(*s, dtype=torch.bfloat16) * 0.05)(D, D)),
        }
    _A_in = _A_setup()

    def _B_setup():
        B, S, D, F = 1, 2048, 512, 1376
        return {
            "x": _w((lambda *s: torch.randn(*s, dtype=torch.bfloat16) * 0.05)(B, S, D)),
            "w1": _w((lambda *s: torch.randn(*s, dtype=torch.bfloat16) * 0.8)(D, F) * (D ** -0.5)),
            "b1": _w((lambda *s: torch.randn(*s, dtype=torch.bfloat16) * 0.4)(F)),
            "w2": _w((lambda *s: torch.randn(*s, dtype=torch.bfloat16) * 0.1)(F, D) * (F ** -0.5)),
        }
    _B_in = _B_setup()

    return {
        "A_x": _A_in["x"],
        "A_wqkv": _A_in["wqkv"],
        "A_wo": _A_in["wo"],
        "B_x": _B_in["x"],
        "B_w1": _B_in["w1"],
        "B_b1": _B_in["b1"],
        "B_w2": _B_in["w2"],
    }

def reference(A_x, A_wqkv, A_wo, B_x, B_w1, B_b1, B_w2):
    def _A_ref(x, wqkv, wo):
        B, S, D = x.shape
        H = 32; Dh = D // H
        qkv = (lambda x, *d: x.permute(*d))((x @ wqkv).reshape(B, S, 3, H, Dh), 2, 0, 3, 1, 4)
        q, k, v = qkv[0], qkv[1], qkv[2]
        phi = lambda t: torch.where(t > 0, t + 1, torch.exp(t)) + 1e-6
        pq, pk = phi(q), phi(k)
        kv = torch.einsum("bhsd,bhse->bhde", pk, v)
        z = torch.einsum("bhsd->bhd", pk)
        num = torch.einsum("bhqd,bhde->bhqe", pq, kv)
        den = torch.einsum("bhqd,bhd->bhq", pq, z)[..., None] + 1e-6
        o = num / den
        return (lambda x, *d: x.permute(*d))(o, 0, 2, 1, 3).reshape(B, S, D) @ wo

    def _B_ref(x, w1, b1, w2):
        h = torch.einsum("bsd,df->bsf", x, w1) + b1
        sp = torch.log1p(torch.exp(-torch.abs(h))) + torch.where(h > 0, h, torch.zeros_like(h))
        act = h * torch.tanh(sp)
        return torch.einsum("bsf,fd->bsd", act, w2)

    x = A_x
    xn = _layernorm(x, axis=-1)
    return x + _A_ref(xn, A_wqkv, A_wo) + _B_ref(xn, B_w1, B_b1, B_w2)
```

```cpp
#include <cuda_runtime.h>
#include <cuda.h>
#include <cuda_bf16.h>
#include <stdint.h>

namespace {

constexpr int S_ = 2048, D_ = 512, F_ = 1376;
constexpr int NCTA = 128;
constexpr int NSTG = 6;
constexpr int STG_BYTES = 16384;
constexpr uint32_t SM_RING = 0;
constexpr uint32_t SM_XA = NSTG * STG_BYTES;
constexpr uint32_t SM_MISC = SM_XA + 131072;
constexpr uint32_t B_XFULL = SM_MISC + 0;
constexpr uint32_t B_FULL = SM_MISC + 64;
constexpr uint32_t B_EMPTY = SM_MISC + 112;
constexpr uint32_t B_PF = SM_MISC + 160;
constexpr uint32_t B_PO = SM_MISC + 224;
constexpr uint32_t B_KVST = SM_MISC + 288;
constexpr uint32_t B_KVFREE = SM_MISC + 304;
constexpr uint32_t B_KVRDY = SM_MISC + 320;
constexpr uint32_t B_DONE = SM_MISC + 328;
constexpr uint32_t SM_BIAS = SM_MISC + 512;
constexpr uint32_t SM_KVF = SM_XA + 61440;
constexpr uint32_t SM_TOTAL = SM_BIAS + 768;
constexpr int SMEM_BYTES = SM_TOTAL + 1024;
constexpr uint32_t A2_WARP = 15360;
constexpr int KV_FLOATS = 4 * 272;
constexpr int SPIN_LIMIT = 1 << 16;

struct alignas(64) Maps { CUtensorMap x, wqkv, w1, w2, w2b, wo, oinit, ored; };

__device__ unsigned g_count;
__device__ __align__(16) float g_kv[2][8][KV_FLOATS];
#define TS(role, i)
#define TSH(i)

__device__ __forceinline__ uint32_t smem_u32(const void* p) { return (uint32_t)__cvta_generic_to_shared(p); }
__device__ __forceinline__ void mbar_init(uint32_t bar, uint32_t cnt) { asm volatile("mbarrier.init.shared::cta.b64 [%0], %1;" ::"r"(bar), "r"(cnt) : "memory"); }
__device__ __forceinline__ void mbar_expect_tx(uint32_t bar, uint32_t bytes) { asm volatile("mbarrier.arrive.expect_tx.shared::cta.b64 _, [%0], %1;" ::"r"(bar), "r"(bytes) : "memory"); }
__device__ __forceinline__ void mbar_arrive(uint32_t bar) { asm volatile("mbarrier.arrive.shared::cta.b64 _, [%0];" ::"r"(bar) : "memory"); }
__device__ __forceinline__ uint32_t mapa(uint32_t addr, uint32_t cta) { uint32_t r; asm("mapa.shared::cluster.u32 %0, %1, %2;" : "=r"(r) : "r"(addr), "r"(cta)); return r; }
__device__ __forceinline__ void mbar_arrive_remote(uint32_t raddr) { asm volatile("mbarrier.arrive.shared::cluster.b64 _, [%0];" ::"r"(raddr) : "memory"); }
__device__ __forceinline__ void mbar_wait(uint32_t bar, uint32_t parity) {
    asm volatile("{.reg .pred p; .reg .u32 it;\n"
                 "mbarrier.try_wait.parity.shared::cta.b64 p, [%0], %1;\n"
                 "@p bra DONE;\n"
                 "mov.u32 it, 0;\n"
                 "LOOP: mbarrier.try_wait.parity.shared::cta.b64 p, [%0], %1;\n"
                 "@p bra DONE;\n"
                 "add.u32 it, it, 1;\n"
                 "setp.lt.u32 p, it, %2;\n"
                 "@p bra LOOP;\n"
                 "trap;\n"
                 "DONE: }" ::"r"(bar), "r"(parity), "n"(SPIN_LIMIT) : "memory");
}
__device__ __forceinline__ void mbar_wait_cluster(uint32_t bar, uint32_t parity) {
    asm volatile("{.reg .pred p; .reg .u32 it;\n"
                 "mov.u32 it, 0;\n"
                 "LOOP: mbarrier.try_wait.parity.acquire.cluster.shared::cta.b64 p, [%0], %1;\n"
                 "@p bra DONE;\n"
                 "add.u32 it, it, 1;\n"
                 "setp.lt.u32 p, it, %2;\n"
                 "@p bra LOOP;\n"
                 "trap;\n"
                 "DONE: }" ::"r"(bar), "r"(parity), "n"(SPIN_LIMIT) : "memory");
}
__device__ __forceinline__ void tma2d(uint32_t dst, const CUtensorMap* m, int c0, int c1, uint32_t bar) {
    asm volatile("cp.async.bulk.tensor.2d.shared::cluster.global.mbarrier::complete_tx::bytes [%0], [%1, {%3,%4}], [%2];" ::"r"(dst), "l"(m), "r"(bar), "r"(c0), "r"(c1) : "memory");
}
__device__ __forceinline__ void tma3d(uint32_t dst, const CUtensorMap* m, int c0, int c1, int c2, uint32_t bar) {
    asm volatile("cp.async.bulk.tensor.3d.shared::cluster.global.mbarrier::complete_tx::bytes [%0], [%1, {%3,%4,%5}], [%2];" ::"r"(dst), "l"(m), "r"(bar), "r"(c0), "r"(c1), "r"(c2) : "memory");
}
__device__ __forceinline__ void tma_store2d(const CUtensorMap* m, int c0, int c1, uint32_t src) {
    asm volatile("cp.async.bulk.tensor.2d.global.shared::cta.bulk_group [%0, {%2,%3}], [%1];" ::"l"(m), "r"(src), "r"(c0), "r"(c1) : "memory");
}
__device__ __forceinline__ void tma_red2d(const CUtensorMap* m, int c0, int c1, uint32_t src) {
    asm volatile("cp.reduce.async.bulk.tensor.2d.global.shared::cta.add.bulk_group [%0, {%2,%3}], [%1];" ::"l"(m), "r"(src), "r"(c0), "r"(c1) : "memory");
}
__device__ __forceinline__ void bulk_s2c(uint32_t rdst, uint32_t src, uint32_t bytes, uint32_t rbar) {
    asm volatile("cp.async.bulk.shared::cluster.shared::cta.mbarrier::complete_tx::bytes [%0], [%1], %2, [%3];" ::"r"(rdst), "r"(src), "r"(bytes), "r"(rbar) : "memory");
}
__device__ __forceinline__ void fence_async_smem() { asm volatile("fence.proxy.async.shared::cta;" ::: "memory"); }
__device__ __forceinline__ void fence_async_all() { asm volatile("fence.proxy.async;" ::: "memory"); }
__device__ __forceinline__ void bar_sync(int id, int n) { asm volatile("bar.sync %0, %1;" ::"r"(id), "r"(n) : "memory"); }
__device__ __forceinline__ void bar_arrive(int id, int n) { asm volatile("bar.arrive %0, %1;" ::"r"(id), "r"(n) : "memory"); }
__device__ __forceinline__ void ldsm4(uint32_t& a, uint32_t& b, uint32_t& c, uint32_t& d, uint32_t addr) {
    asm volatile("ldmatrix.sync.aligned.m8n8.x4.shared.b16 {%0,%1,%2,%3}, [%4];" : "=r"(a), "=r"(b), "=r"(c), "=r"(d) : "r"(addr) : "memory");
}
__device__ __forceinline__ void ldsm4t(uint32_t& a, uint32_t& b, uint32_t& c, uint32_t& d, uint32_t addr) {
    asm volatile("ldmatrix.sync.aligned.m8n8.x4.trans.shared.b16 {%0,%1,%2,%3}, [%4];" : "=r"(a), "=r"(b), "=r"(c), "=r"(d) : "r"(addr) : "memory");
}
__device__ __forceinline__ void stsm4(uint32_t addr, uint32_t a, uint32_t b, uint32_t c, uint32_t d) {
    asm volatile("stmatrix.sync.aligned.m8n8.x4.shared.b16 [%0], {%1,%2,%3,%4};" ::"r"(addr), "r"(a), "r"(b), "r"(c), "r"(d) : "memory");
}
__device__ __forceinline__ void lds4(uint32_t& a, uint32_t& b, uint32_t& c, uint32_t& d, uint32_t addr) {
    asm volatile("ld.shared.v4.u32 {%0,%1,%2,%3}, [%4];" : "=r"(a), "=r"(b), "=r"(c), "=r"(d) : "r"(addr) : "memory");
}
__device__ __forceinline__ void lds4f(float& a, float& b, float& c, float& d, uint32_t addr) {
    asm volatile("ld.shared.v4.f32 {%0,%1,%2,%3}, [%4];" : "=f"(a), "=f"(b), "=f"(c), "=f"(d) : "r"(addr) : "memory");
}
__device__ __forceinline__ void sts4(uint32_t addr, uint32_t a, uint32_t b, uint32_t c, uint32_t d) {
    asm volatile("st.shared.v4.u32 [%0], {%1,%2,%3,%4};" ::"r"(addr), "r"(a), "r"(b), "r"(c), "r"(d) : "memory");
}
__device__ __forceinline__ uint32_t pack2(float lo, float hi) {
    uint32_t r;
    asm("cvt.rn.bf16x2.f32 %0, %1, %2;" : "=r"(r) : "f"(hi), "f"(lo));
    return r;
}
__device__ __forceinline__ void mma16816(float (&c)[4], uint32_t a0, uint32_t a1, uint32_t a2, uint32_t a3, uint32_t b0, uint32_t b1) {
    asm("mma.sync.aligned.m16n8k16.row.col.f32.bf16.bf16.f32 {%0,%1,%2,%3}, {%4,%5,%6,%7}, {%8,%9}, {%0,%1,%2,%3};"
        : "+f"(c[0]), "+f"(c[1]), "+f"(c[2]), "+f"(c[3]) : "r"(a0), "r"(a1), "r"(a2), "r"(a3), "r"(b0), "r"(b1));
}
__device__ __forceinline__ float ex2f(float x) { float y; asm("ex2.approx.ftz.f32 %0, %1;" : "=f"(y) : "f"(x)); return y; }
__device__ __forceinline__ float rcpf(float x) { float y; asm("rcp.approx.ftz.f32 %0, %1;" : "=f"(y) : "f"(x)); return y; }
__device__ __forceinline__ void wg_fence() { asm volatile("wgmma.fence.sync.aligned;" ::: "memory"); }
__device__ __forceinline__ void wg_commit() { asm volatile("wgmma.commit_group.sync.aligned;" ::: "memory"); }
template <int N> __device__ __forceinline__ void wg_wait() { asm volatile("wgmma.wait_group.sync.aligned %0;" ::"n"(N) : "memory"); }

template <int N, int ACC> __device__ __forceinline__ void wgmma_rs(float (&d)[32], const uint32_t* a, uint64_t db) {
    if constexpr (N == 64) {
        asm volatile("{.reg .pred p; setp.ne.b32 p, %37, 0;\n"
            "wgmma.mma_async.sync.aligned.m64n64k16.f32.bf16.bf16 {%0,%1,%2,%3,%4,%5,%6,%7,%8,%9,%10,%11,%12,%13,%14,%15,%16,%17,%18,%19,%20,%21,%22,%23,%24,%25,%26,%27,%28,%29,%30,%31}, {%32,%33,%34,%35}, %36, p, 1, 1, 1;}\n"
            : "+f"(d[0]), "+f"(d[1]), "+f"(d[2]), "+f"(d[3]), "+f"(d[4]), "+f"(d[5]), "+f"(d[6]), "+f"(d[7]), "+f"(d[8]), "+f"(d[9]), "+f"(d[10]), "+f"(d[11]), "+f"(d[12]), "+f"(d[13]), "+f"(d[14]), "+f"(d[15]),
              "+f"(d[16]), "+f"(d[17]), "+f"(d[18]), "+f"(d[19]), "+f"(d[20]), "+f"(d[21]), "+f"(d[22]), "+f"(d[23]), "+f"(d[24]), "+f"(d[25]), "+f"(d[26]), "+f"(d[27]), "+f"(d[28]), "+f"(d[29]), "+f"(d[30]), "+f"(d[31])
            : "r"(a[0]), "r"(a[1]), "r"(a[2]), "r"(a[3]), "l"(db), "n"(ACC));
    } else {
        asm volatile("{.reg .pred p; setp.ne.b32 p, %29, 0;\n"
            "wgmma.mma_async.sync.aligned.m64n48k16.f32.bf16.bf16 {%0,%1,%2,%3,%4,%5,%6,%7,%8,%9,%10,%11,%12,%13,%14,%15,%16,%17,%18,%19,%20,%21,%22,%23}, {%24,%25,%26,%27}, %28, p, 1, 1, 1;}\n"
            : "+f"(d[0]), "+f"(d[1]), "+f"(d[2]), "+f"(d[3]), "+f"(d[4]), "+f"(d[5]), "+f"(d[6]), "+f"(d[7]), "+f"(d[8]), "+f"(d[9]), "+f"(d[10]), "+f"(d[11]), "+f"(d[12]), "+f"(d[13]), "+f"(d[14]), "+f"(d[15]),
              "+f"(d[16]), "+f"(d[17]), "+f"(d[18]), "+f"(d[19]), "+f"(d[20]), "+f"(d[21]), "+f"(d[22]), "+f"(d[23])
            : "r"(a[0]), "r"(a[1]), "r"(a[2]), "r"(a[3]), "l"(db), "n"(ACC));
    }
}

struct Ring { uint32_t slot, phase; };

template <int N, int K0, int NK, bool FIRST>
__device__ __forceinline__ void mma_stage(float (&d)[32], const uint32_t (&A)[128], Ring& r, uint32_t sb, uint64_t desc0, int lane) {
    mbar_wait(sb + B_FULL + r.slot * 8, r.phase);
    const uint64_t db = desc0 + (uint64_t)(r.slot * (STG_BYTES >> 4));
    if (FIRST) wg_fence();
#pragma unroll
    for (int k = 0; k < NK; ++k) {
        if (FIRST && k == 0) wgmma_rs<N, 0>(d, &A[(K0 + k) * 4], db + k * 128);
        else wgmma_rs<N, 1>(d, &A[(K0 + k) * 4], db + k * 128);
    }
    wg_commit();
    if (!FIRST) {
        wg_wait<1>();
        const uint32_t prev = r.slot == 0 ? NSTG - 1 : r.slot - 1;
        if (lane == 0) mbar_arrive(sb + B_EMPTY + prev * 8);
    }
    if (++r.slot == NSTG) { r.slot = 0; r.phase ^= 1; }
}
__device__ __forceinline__ void mma_finish(const Ring& r, uint32_t sb, int lane) {
    wg_wait<0>();
    const uint32_t prev = r.slot == 0 ? NSTG - 1 : r.slot - 1;
    if (lane == 0) mbar_arrive(sb + B_EMPTY + prev * 8);
}

constexpr float LOG2E = 1.4426950408889634f;
__device__ __forceinline__ float phi(float a, float rs, float rl) {
    const float e = ex2f(fminf(a, 0.f) * rl);
    return fmaf(fmaxf(a, 0.f), rs, e + 1e-6f);
}
__device__ __forceinline__ float mish(float h) {
    const float e = ex2f(fminf(h * LOG2E, 40.f));
    const float u = e + 2.f;
    const float n = e * u;
    return h * (n * rcpf(fmaf(e, u, 2.f)));
}

__global__ void __cluster_dims__(2, 1, 1) __launch_bounds__(384, 1)
fused_kernel(const __grid_constant__ Maps maps, const __nv_bfloat16* __restrict__ b1) {
    extern __shared__ uint8_t smem_raw[];
    const uint32_t sb = (smem_u32(smem_raw) + 1023u) & ~1023u;
    const int warp = __shfl_sync(0xffffffffu, (int)(threadIdx.x >> 5), 0);
    const int lane = threadIdx.x & 31;
    const int rank = blockIdx.x & 1;
    int mi, pr;
    {
        const int c = blockIdx.x >> 1;
        int g, m;
        if (c < 4) { g = 15; m = c; }
        else if (c < 36) { g = (c - 4) & 7; m = (c - 4) >> 3; }
        else { m = ((c - 36) * 37) >> 8; g = 8 + (c - 36) - 7 * m; }
        mi = (g & ~1) | (m & 1);
        pr = (g & 1) * 2 + (m >> 1);
    }
    const int j = pr * 2 + rank;
    const int row0 = mi * 128;

    if (warp >= 8) {
        asm volatile("setmaxnreg.dec.sync.aligned.u32 56;");
        if (warp == 8) {
            if (lane == 0) {
#pragma unroll
                for (int i = 0; i < 8; ++i) mbar_init(sb + B_XFULL + i * 8, 1);
#pragma unroll
                for (int i = 0; i < NSTG; ++i) mbar_init(sb + B_FULL + i * 8, 1);
                fence_async_smem();
            }
            __syncwarp();
            bar_arrive(3, 384);
            asm volatile("barrier.cluster.arrive.relaxed.aligned;" ::: "memory");
            if (lane == 0) {
#pragma unroll
                for (int i = 0; i < 8; ++i) {
                    mbar_expect_tx(sb + B_XFULL + i * 8, 16384);
                    tma3d(sb + SM_XA + i * 16384, &maps.x, 0, row0 + (i >> 2) * 64, (i & 3) * 2, sb + B_XFULL + i * 8);
                }
#pragma unroll
                for (int i = 0; i < NSTG; ++i) mbar_init(sb + B_EMPTY + i * 8, 8);
                uint32_t slot = 0, phase = 1;
#pragma unroll 1
                for (int g = 0; g < 40; ++g) {
                    const int s = g & 3, c = g >> 2;
                    const CUtensorMap* m;
                    int col, row;
                    uint32_t bytes = STG_BYTES;
                    if (c < 6) {
                        row = s * 128;
                        if (c >= 2 && c < 5) { m = &maps.w1; col = 176 * j + 64 * (c - 2); }
                        else { m = &maps.wqkv; col = 64 * j + (c == 5 ? 0 : 512 * (c + 1)); }
                    } else {
                        col = 256 * rank + 64 * (c - 6);
                        if (s == 3) { m = &maps.wo; row = 128 * pr; }
                        else { row = 352 * pr + 128 * s; m = &maps.w2; if (s == 2) { m = &maps.w2b; bytes = 96 * 128; } }
                    }
                    if (g >= NSTG) mbar_wait(sb + B_EMPTY + slot * 8, phase);
                    mbar_expect_tx(sb + B_FULL + slot * 8, bytes);
                    tma2d(sb + SM_RING + slot * STG_BYTES, m, col, row, sb + B_FULL + slot * 8);
                    if (++slot == NSTG) { slot = 0; phase ^= 1; }
                }
            }
            __syncwarp();
            asm volatile("barrier.cluster.wait.aligned;" ::: "memory");
            if (lane == 0) mbar_wait_cluster(sb + B_DONE, 0);
        } else if (warp == 11) {
            const unsigned epoch = *(volatile unsigned*)&g_count >> 8;
            bar_arrive(3, 384);
#pragma unroll
            for (int f = 0; f < 3; ++f) {
                const int col = 64 * f + 2 * lane;
                float lo = 0.f, hi = 0.f;
                if (col < 176 && 176 * j + col < F_) {
                    const uint32_t v = *(const uint32_t*)(b1 + 176 * j + col);
                    lo = __uint_as_float(v << 16);
                    hi = __uint_as_float(v & 0xffff0000u);
                }
                const uint32_t a = sb + SM_BIAS + f * 256 + (lane >> 3) * 64 + (lane & 3) * 16 + ((lane >> 2) & 1) * 8;
                asm volatile("st.shared.v2.f32 [%0], {%1,%2};" ::"r"(a), "f"(lo), "f"(hi) : "memory");
            }
            if (lane < 17) *(float4*)&g_kv[(epoch & 1) ^ 1][j][mi * 68 + lane * 4] = make_float4(0.f, 0.f, 0.f, 0.f);
            asm volatile("barrier.cluster.arrive.release.aligned; barrier.cluster.wait.aligned;" ::: "memory");
        } else {
            const int hw = warp - 9;
            const unsigned epoch = *(volatile unsigned*)&g_count >> 8;
            if (lane == 0) {
                if (hw == 0) {
#pragma unroll
                    for (int i = 0; i < 8; ++i) { mbar_init(sb + B_PF + i * 8, 1); mbar_init(sb + B_PO + i * 8, 1); }
#pragma unroll
                    for (int i = 0; i < 8; ++i) { mbar_expect_tx(sb + B_PF + i * 8, 11 * 512); mbar_expect_tx(sb + B_PO + i * 8, 4 * 512); }
                } else {
                    mbar_init(sb + B_KVST, 4); mbar_init(sb + B_KVST + 8, 4);
                    mbar_init(sb + B_KVFREE, 2); mbar_init(sb + B_KVFREE + 8, 2);
                    mbar_init(sb + B_KVRDY, 2);
                    mbar_init(sb + B_DONE, 8);
                }
                asm volatile("fence.mbarrier_init.release.cluster;" ::: "memory");
            }
            __syncwarp();
            bar_sync(3, 384);
            if (hw == 0 && lane == 0) {
                mbar_wait(sb + B_XFULL + (j >> 1) * 8, 0);
                tma_store2d(&maps.oinit, 64 * j, row0, sb + SM_XA + j * 8192);
                mbar_wait(sb + B_XFULL + (4 + (j >> 1)) * 8, 0);
                tma_store2d(&maps.oinit, 64 * j, row0 + 64, sb + SM_XA + 65536 + j * 8192);
                asm volatile("cp.async.bulk.commit_group; cp.async.bulk.wait_group.read 0;" ::: "memory");
            }
            __syncwarp();
            TSH(hw * 8 + 0);
            asm volatile("barrier.cluster.arrive.relaxed.aligned; barrier.cluster.wait.aligned;" ::: "memory");
            float c0[2][4], c1[2][4], cz[2][4];
#pragma unroll
            for (int h = 0; h < 2; ++h)
#pragma unroll
                for (int i = 0; i < 4; ++i) c0[h][i] = c1[h][i] = cz[h][i] = 0.f;
            const int lrow = (lane & 7) + ((lane >> 4) << 3);
            const uint32_t loff = lrow * 128 + (((hw * 4 + ((lane >> 3) & 1)) ^ (lane & 7)) << 4);
#pragma unroll 1
            for (int g = 0; g < 2; ++g) {
                mbar_wait(sb + B_KVST + g * 8, 0);
                TSH(hw * 8 + 1 + g);
#pragma unroll 1
                for (int wl = 0; wl < 4; ++wl) {
                    const uint32_t base = sb + SM_XA + g * 65536 + wl * A2_WARP + rank * 5632;
#pragma unroll
                    for (int h = 0; h < 2; ++h) {
                        uint32_t a0, a1, a2, a3, v0, v1, v2, v3;
                        ldsm4t(a0, a1, a2, a3, base + (loff ^ (h << 5)));
                        ldsm4t(v0, v1, v2, v3, base + 2048 + (loff ^ (h << 5)));
                        mma16816(c0[h], a0, a1, a2, a3, v0, v2);
                        mma16816(c1[h], a0, a1, a2, a3, v1, v3);
                        mma16816(cz[h], a0, a1, a2, a3, 0x3f803f80u, 0x3f803f80u);
                    }
                }
                __syncwarp();
                if (lane == 0) mbar_arrive(sb + B_KVFREE + g * 8);
            }
            float* gk = &g_kv[epoch & 1][j][hw * 2 * 272];
#pragma unroll
            for (int h = 0; h < 2; ++h) {
                asm volatile("red.relaxed.gpu.global.add.v4.f32 [%0], {%1,%2,%3,%4};" ::"l"(gk + h * 272 + lane * 4), "f"(c0[h][0]), "f"(c0[h][1]), "f"(c0[h][2]), "f"(c0[h][3]) : "memory");
                asm volatile("red.relaxed.gpu.global.add.v4.f32 [%0], {%1,%2,%3,%4};" ::"l"(gk + h * 272 + 128 + lane * 4), "f"(c1[h][0]), "f"(c1[h][1]), "f"(c1[h][2]), "f"(c1[h][3]) : "memory");
                if ((lane & 3) == 0) {
                    asm volatile("red.relaxed.gpu.global.add.f32 [%0], %1;" ::"l"(gk + h * 272 + 256 + (lane >> 2)), "f"(cz[h][0]) : "memory");
                    asm volatile("red.relaxed.gpu.global.add.f32 [%0], %1;" ::"l"(gk + h * 272 + 264 + (lane >> 2)), "f"(cz[h][2]) : "memory");
                }
            }
            __syncwarp();
            TSH(hw * 8 + 3);
            if (lane == 0) {
                if (hw == 0) { asm volatile("cp.async.bulk.wait_group 0;" ::: "memory"); fence_async_all(); }
                asm volatile("fence.acq_rel.gpu; red.relaxed.gpu.global.add.u32 [%0], 1;" ::"l"(&g_count) : "memory");
            }
            __syncwarp();
            TSH(hw * 8 + 4);
            const unsigned target = (epoch + 1) << 8;
            for (int it = 0;; ++it) {
                unsigned v;
                asm volatile("ld.acquire.gpu.global.u32 %0, [%1];" : "=r"(v) : "l"(&g_count) : "memory");
                if ((int)(v - target) >= 0) break;
                if (it > SPIN_LIMIT) asm volatile("trap;");
            }
            TSH(hw * 8 + 5);
#pragma unroll
            for (int h = 0; h < 2; ++h) {
                const float4 t0 = __ldcg((const float4*)(gk + h * 272 + lane * 4));
                const float4 t1 = __ldcg((const float4*)(gk + h * 272 + 128 + lane * 4));
                const float2 z0 = __ldcg((const float2*)(gk + h * 272 + 256 + (lane & 3) * 2));
                const float2 z1 = __ldcg((const float2*)(gk + h * 272 + 264 + (lane & 3) * 2));
                uint32_t p[4] = {pack2(t0.x, t0.y), pack2(t0.z, t0.w), pack2(t1.x, t1.y), pack2(t1.z, t1.w)};
#pragma unroll
                for (int i = 0; i < 4; ++i) asm volatile("movmatrix.sync.aligned.m8n8.trans.b16 %0, %0;" : "+r"(p[i]));
                sts4(sb + SM_KVF + (hw * 2 + h) * 512 + lane * 16, p[0], p[1], p[2], p[3]);
                if (lane < 4) asm volatile("st.shared.v2.u32 [%0], {%1,%2};" ::"r"(sb + SM_KVF + 2048 + hw * 64 + lane * 16 + h * 8), "r"(pack2(z0.x, z0.y)), "r"(pack2(z1.x, z1.y)) : "memory");
            }
            __syncwarp();
            if (lane == 0) mbar_arrive(sb + B_KVRDY);
            TSH(hw * 8 + 6);
        }
    } else {
        asm volatile("setmaxnreg.inc.sync.aligned.u32 224;");
        const int g = warp >> 2, wl = warp & 3;
        const int q = lane & 3;
        uint32_t A[128];
        float d[32];
        float rs0, rs1;
        const uint32_t swz = (lane & 15) * 128 + (((lane >> 4) ^ (lane & 7)) << 4);
        bar_sync(3, 384);
        {
            float st[4][4];
#pragma unroll
            for (int i = 0; i < 4; ++i)
#pragma unroll
                for (int k = 0; k < 4; ++k) st[i][k] = 0.f;
            const uint32_t xb = sb + SM_XA + g * 65536 + wl * 2048;
#pragma unroll
            for (int e = 0; e < 4; ++e) {
                mbar_wait(sb + B_XFULL + (g * 4 + e) * 8, 0);
                TS(g, e);
#pragma unroll
                for (int t = 0; t < 8; ++t) {
                    const int s = e * 8 + t;
                    ldsm4(A[4 * s], A[4 * s + 1], A[4 * s + 2], A[4 * s + 3], xb + (s >> 2) * 8192 + (swz ^ ((s & 3) << 5)));
                }
#pragma unroll
                for (int t = 0; t < 8; ++t) {
                    const int s = e * 8 + t;
                    mma16816(st[(t & 1) * 2], A[4 * s], 0x3f803f80u, A[4 * s + 2], 0x3f803f80u, A[4 * s], A[4 * s + 2]);
                    mma16816(st[(t & 1) * 2 + 1], A[4 * s + 1], 0x3f803f80u, A[4 * s + 3], 0x3f803f80u, A[4 * s + 1], A[4 * s + 3]);
                }
            }
            const int r = lane >> 2;
            const int src = 4 * r + (r >> 1);
            const bool odd = r & 1;
            const float q0 = __shfl_sync(0xffffffffu, odd ? st[0][1] + st[2][1] : st[0][0] + st[2][0], src);
            const float s0 = __shfl_sync(0xffffffffu, odd ? st[0][3] + st[2][3] : st[0][2] + st[2][2], src);
            const float q1 = __shfl_sync(0xffffffffu, odd ? st[1][1] + st[3][1] : st[1][0] + st[3][0], src);
            const float s1 = __shfl_sync(0xffffffffu, odd ? st[1][3] + st[3][3] : st[1][2] + st[3][2], src);
            asm volatile("barrier.cluster.arrive.relaxed.aligned;" ::: "memory");
            const float m0 = s0 * (1.f / D_), m1 = s1 * (1.f / D_);
            rs0 = rsqrtf(fmaxf(fmaf(q0, 1.f / D_, -m0 * m0), 0.f) + 1e-5f);
            rs1 = rsqrtf(fmaxf(fmaf(q1, 1.f / D_, -m1 * m1), 0.f) + 1e-5f);
            const uint32_t mm0 = pack2(m0, m0), mm1 = pack2(m1, m1);
#pragma unroll
            for (int i = 0; i < 128; ++i) asm("sub.rn.bf16x2 %0, %0, %1;" : "+r"(A[i]) : "r"((i & 1) ? mm1 : mm0));
        }
        TS(g, 4);
        const uint64_t desc0 = ((uint64_t)0x40000040u << 32) | (1u << 16) | (((sb + SM_RING) & 0x3FFFFu) >> 4);
        const uint32_t a2 = sb + SM_XA + g * 65536 + wl * A2_WARP;
        Ring ring{0, 0};
#pragma unroll 1
        for (int c = 0;; ++c) {
            if (c + g != 0) bar_sync(1 + g, 256);
            TS(g, 8 + c * 3);
            if (c != 4) {
                mma_stage<64, 0, 8, true>(d, A, ring, sb, desc0, lane);
                mma_stage<64, 8, 8, false>(d, A, ring, sb, desc0, lane);
                mma_stage<64, 16, 8, false>(d, A, ring, sb, desc0, lane);
                mma_stage<64, 24, 8, false>(d, A, ring, sb, desc0, lane);
            } else {
                mma_stage<48, 0, 8, true>(d, A, ring, sb, desc0, lane);
                mma_stage<48, 8, 8, false>(d, A, ring, sb, desc0, lane);
                mma_stage<48, 16, 8, false>(d, A, ring, sb, desc0, lane);
                mma_stage<48, 24, 8, false>(d, A, ring, sb, desc0, lane);
            }
            bar_arrive(2 - g, 256);
            mma_finish(ring, sb, lane);
            TS(g, 9 + c * 3);
            if (c == 5) break;
            if (c == 0) {
                const float rl0 = rs0 * LOG2E, rl1 = rs1 * LOG2E;
                asm volatile("barrier.cluster.wait.aligned;" ::: "memory");
#pragma unroll
                for (int u = 0; u < 4; ++u)
                    stsm4(a2 + rank * 5632 + (swz ^ (u << 5)),
                          pack2(phi(d[8 * u], rs0, rl0), phi(d[8 * u + 1], rs0, rl0)), pack2(phi(d[8 * u + 2], rs1, rl1), phi(d[8 * u + 3], rs1, rl1)),
                          pack2(phi(d[8 * u + 4], rs0, rl0), phi(d[8 * u + 5], rs0, rl0)), pack2(phi(d[8 * u + 6], rs1, rl1), phi(d[8 * u + 7], rs1, rl1)));
            } else if (c == 1) {
#pragma unroll
                for (int u = 0; u < 4; ++u)
                    stsm4(a2 + rank * 5632 + 2048 + (swz ^ (u << 5)),
                          pack2(d[8 * u] * rs0, d[8 * u + 1] * rs0), pack2(d[8 * u + 2] * rs1, d[8 * u + 3] * rs1),
                          pack2(d[8 * u + 4] * rs0, d[8 * u + 5] * rs0), pack2(d[8 * u + 6] * rs1, d[8 * u + 7] * rs1));
                __syncwarp();
                if (lane == 0) mbar_arrive(sb + B_KVST + g * 8);
            } else {
                const int f = c - 2;
                const uint32_t dst = a2 + rank * 5632 + f * 2048;
                if (f == 0) mbar_wait(sb + B_KVFREE + g * 8, 0);
#pragma unroll
                for (int u = 0; u < 4; ++u) {
                    if (u < 3 || f != 2) {
                        float b0, b1v, b2, b3;
                        lds4f(b0, b1v, b2, b3, sb + SM_BIAS + f * 256 + u * 64 + q * 16);
                        sts4(dst + u * 512 + lane * 16,
                             pack2(mish(fmaf(d[8 * u], rs0, b0)), mish(fmaf(d[8 * u + 1], rs0, b1v))), pack2(mish(fmaf(d[8 * u + 2], rs1, b0)), mish(fmaf(d[8 * u + 3], rs1, b1v))),
                             pack2(mish(fmaf(d[8 * u + 4], rs0, b2)), mish(fmaf(d[8 * u + 5], rs0, b3))), pack2(mish(fmaf(d[8 * u + 6], rs1, b2)), mish(fmaf(d[8 * u + 7], rs1, b3))));
                    }
                }
                fence_async_smem();
                __syncwarp();
                if (lane == 0) bulk_s2c(mapa(dst, rank ^ 1), dst, f == 2 ? 1536 : 2048, mapa(sb + B_PF + warp * 8, rank ^ 1));
            }
            TS(g, 10 + c * 3);
        }
        {
            const float rl0 = rs0 * LOG2E, rl1 = rs1 * LOG2E;
            mbar_wait_cluster(sb + B_PF + warp * 8, 0);
#pragma unroll
            for (int s = 0; s < 8; ++s) lds4(A[4 * s], A[4 * s + 1], A[4 * s + 2], A[4 * s + 3], a2 + s * 512 + lane * 16);
            uint32_t pq[16];
#pragma unroll
            for (int u = 0; u < 4; ++u) {
                pq[4 * u] = pack2(phi(d[8 * u], rs0, rl0), phi(d[8 * u + 1], rs0, rl0));
                pq[4 * u + 1] = pack2(phi(d[8 * u + 2], rs1, rl1), phi(d[8 * u + 3], rs1, rl1));
                pq[4 * u + 2] = pack2(phi(d[8 * u + 4], rs0, rl0), phi(d[8 * u + 5], rs0, rl0));
                pq[4 * u + 3] = pack2(phi(d[8 * u + 6], rs1, rl1), phi(d[8 * u + 7], rs1, rl1));
            }
            TS(g, 40);
            mbar_wait(sb + B_KVRDY, 0);
            TS(g, 41);
            const uint32_t dst = a2 + (22 + 4 * rank) * 512;
#pragma unroll
            for (int hp = 0; hp < 2; ++hp) {
                uint32_t z[4];
                lds4(z[0], z[1], z[2], z[3], sb + SM_KVF + 2048 + hp * 64 + q * 16);
#pragma unroll
                for (int i = 0; i < 2; ++i) {
                    const int h = hp * 2 + i;
                    uint32_t k0, k1, k2, k3;
                    lds4(k0, k1, k2, k3, sb + SM_KVF + h * 512 + lane * 16);
                    float n0[4] = {0.f, 0.f, 0.f, 0.f}, n1[4] = {0.f, 0.f, 0.f, 0.f}, dn[4] = {1e-6f, 1e-6f, 1e-6f, 1e-6f};
                    mma16816(dn, pq[4 * h], pq[4 * h + 1], pq[4 * h + 2], pq[4 * h + 3], z[2 * i], z[2 * i + 1]);
                    mma16816(n0, pq[4 * h], pq[4 * h + 1], pq[4 * h + 2], pq[4 * h + 3], k0, k1);
                    mma16816(n1, pq[4 * h], pq[4 * h + 1], pq[4 * h + 2], pq[4 * h + 3], k2, k3);
                    const float i0 = rcpf(dn[0]), i1 = rcpf(dn[2]);
                    sts4(dst + h * 512 + lane * 16, pack2(n0[0] * i0, n0[1] * i0), pack2(n0[2] * i1, n0[3] * i1), pack2(n1[0] * i0, n1[1] * i0), pack2(n1[2] * i1, n1[3] * i1));
                }
            }
            fence_async_smem();
            __syncwarp();
            if (lane == 0) bulk_s2c(mapa(dst, rank ^ 1), dst, 2048, mapa(sb + B_PO + warp * 8, rank ^ 1));
#pragma unroll
            for (int s = 8; s < 22; ++s) lds4(A[4 * s], A[4 * s + 1], A[4 * s + 2], A[4 * s + 3], a2 + s * 512 + lane * 16);
        }
        TS(g, 25);
#pragma unroll
        for (int i = 88; i < 120; ++i) A[i] = 0;
#pragma unroll 1
        for (int c = 0; c < 4; ++c) {
            bar_sync(1 + g, 256);
            TS(g, 26 + c * 3);
            mma_stage<64, 0, 8, true>(d, A, ring, sb, desc0, lane);
            mma_stage<64, 8, 8, false>(d, A, ring, sb, desc0, lane);
            mma_stage<64, 16, 6, false>(d, A, ring, sb, desc0, lane);
            if (c == 0) {
                mbar_wait_cluster(sb + B_PO + warp * 8, 0);
#pragma unroll
                for (int s = 22; s < 30; ++s) lds4(A[4 * s], A[4 * s + 1], A[4 * s + 2], A[4 * s + 3], a2 + s * 512 + lane * 16);
                if (lane == 0) mbar_arrive_remote(mapa(sb + B_DONE, rank ^ 1));
                wg_fence();
            }
            mma_stage<64, 22, 8, false>(d, A, ring, sb, desc0, lane);
            if (c + g != 4) bar_arrive(2 - g, 256);
            mma_finish(ring, sb, lane);
            TS(g, 27 + c * 3);
            const uint32_t stg = a2 + (c == 2 ? 13312 - rank * 2048 : (rank ? 0 : 6144) + (c & 1 & ~(c >> 1)) * 2048);
            if (c == 3) {
                if (lane == 0) asm volatile("cp.async.bulk.wait_group.read 2;" ::: "memory");
                __syncwarp();
            }
#pragma unroll
            for (int u = 0; u < 4; ++u)
                stsm4(stg + (swz ^ (u << 5)), pack2(d[8 * u], d[8 * u + 1]), pack2(d[8 * u + 2], d[8 * u + 3]), pack2(d[8 * u + 4], d[8 * u + 5]), pack2(d[8 * u + 6], d[8 * u + 7]));
            fence_async_all();
            __syncwarp();
            if (lane == 0) {
                tma_red2d(&maps.ored, 256 * rank + 64 * c, row0 + warp * 16, stg);
                asm volatile("cp.async.bulk.commit_group;" ::: "memory");
            }
            TS(g, 28 + c * 3);
        }
        if (lane == 0) asm volatile("cp.async.bulk.wait_group.read 0;" ::: "memory");
        TS(g, 38);
    }
}

typedef CUresult (*EncodeFn)(CUtensorMap*, CUtensorMapDataType, cuuint32_t, void*, const cuuint64_t*, const cuuint64_t*, const cuuint32_t*, const cuuint32_t*,
                             CUtensorMapInterleave, CUtensorMapSwizzle, CUtensorMapL2promotion, CUtensorMapFloatOOBfill);

void make_map(EncodeFn enc, CUtensorMap* m, const void* base, int rank, const cuuint64_t* dims, const cuuint64_t* strides, const cuuint32_t* box) {
    const cuuint32_t es[3] = {1, 1, 1};
    enc(m, CU_TENSOR_MAP_DATA_TYPE_BFLOAT16, rank, const_cast<void*>(base), dims, strides, box, es, CU_TENSOR_MAP_INTERLEAVE_NONE,
        CU_TENSOR_MAP_SWIZZLE_128B, CU_TENSOR_MAP_L2_PROMOTION_L2_128B, CU_TENSOR_MAP_FLOAT_OOB_FILL_NONE);
}
void make_map2(EncodeFn enc, CUtensorMap* m, const void* base, int cols, int rows, int box_rows) {
    const cuuint64_t dims[2] = {(cuuint64_t)cols, (cuuint64_t)rows};
    const cuuint64_t strides[1] = {(cuuint64_t)cols * 2};
    const cuuint32_t box[2] = {64, (cuuint32_t)box_rows};
    make_map(enc, m, base, 2, dims, strides, box);
}

}

extern "C" void kernel_launch(void* const* d_in, const int* in_sizes, int n_in, void* d_out, int out_size) {
    (void)in_sizes; (void)n_in; (void)out_size;
    static EncodeFn enc = nullptr;
    if (!enc) {
        void* p = nullptr;
        cudaDriverEntryPointQueryResult qr;
        cudaGetDriverEntryPoint("cuTensorMapEncodeTiled", &p, cudaEnableDefault, &qr);
        enc = (EncodeFn)p;
        cudaFuncSetAttribute(fused_kernel, cudaFuncAttributeMaxDynamicSharedMemorySize, SMEM_BYTES);
    }
    Maps maps;
    {
        const cuuint64_t dims[3] = {64, S_, D_ / 64};
        const cuuint64_t strides[2] = {D_ * 2, 128};
        const cuuint32_t box[3] = {64, 64, 2};
        make_map(enc, &maps.x, d_in[0], 3, dims, strides, box);
    }
    make_map2(enc, &maps.wqkv, d_in[1], 3 * D_, D_, 128);
    make_map2(enc, &maps.w1, d_in[4], F_, D_, 128);
    make_map2(enc, &maps.w2, d_in[6], D_, F_, 128);
    make_map2(enc, &maps.w2b, d_in[6], D_, F_, 96);
    make_map2(enc, &maps.wo, d_in[2], D_, D_, 128);
    make_map2(enc, &maps.oinit, d_out, D_, S_, 64);
    make_map2(enc, &maps.ored, d_out, D_, S_, 16);
    fused_kernel<<<NCTA, 384, SMEM_BYTES, cudaStreamPerThread>>>(maps, (const __nv_bfloat16*)d_in[5]);
}
```

```cpp
#include <cuda_runtime.h>
#include <cuda.h>
#include <cuda_bf16.h>
#include <stdint.h>

namespace {

constexpr int S_ = 2048, D_ = 512, F_ = 1376;
constexpr int NCTA = 128;
constexpr int NSTG = 6;
constexpr int STG_BYTES = 16384;
constexpr uint32_t SM_RING = 0;
constexpr uint32_t SM_XA = NSTG * STG_BYTES;
constexpr uint32_t X_PK = SM_XA;
constexpr uint32_t X_KVB = SM_XA + 32768;
constexpr uint32_t X_OWN = SM_XA + 36864;
constexpr uint32_t X_PF = SM_XA + 69632;
constexpr uint32_t X_PL = SM_XA + 102400;
constexpr uint32_t SM_MISC = SM_XA + 131072;
constexpr uint32_t B_XFULL = SM_MISC + 0;
constexpr uint32_t B_FULL = SM_MISC + 64;
constexpr uint32_t B_EMPTY = SM_MISC + 112;
constexpr uint32_t B_PF = SM_MISC + 160;
constexpr uint32_t B_PO = SM_MISC + 224;
constexpr uint32_t B_KVST = SM_MISC + 288;
constexpr uint32_t B_KVRDY = SM_MISC + 296;
constexpr uint32_t B_DONE = SM_MISC + 304;
constexpr uint32_t SM_KVOFF = SM_MISC + 312;
constexpr uint32_t SM_BIAS = SM_MISC + 512;
constexpr uint32_t SM_TOTAL = SM_BIAS + 1536;
constexpr int SMEM_BYTES = SM_TOTAL + 1024;
constexpr int KV_FLOATS = 4 * 272;
constexpr int SPIN_LIMIT = 1 << 16;
constexpr float LOG2E = 1.4426950408889634f, LN2 = 0.6931471805599453f;
constexpr uint32_t ONES2 = 0x3f803f80u;

struct alignas(64) Maps { CUtensorMap x, wqkv, w1, w2, w2b, wo, oinit, ored; uint64_t desc[10]; };

__device__ unsigned g_count;
__device__ __align__(16) float g_kv[2][8][KV_FLOATS];
#define TS(role, i)
#define TSH(i)

__device__ __forceinline__ uint32_t smem_u32(const void* p) { return (uint32_t)__cvta_generic_to_shared(p); }
__device__ __forceinline__ void mbar_init(uint32_t bar, uint32_t cnt) { asm volatile("mbarrier.init.shared::cta.b64 [%0], %1;" ::"r"(bar), "r"(cnt) : "memory"); }
__device__ __forceinline__ void mbar_expect_tx(uint32_t bar, uint32_t bytes) { asm volatile("mbarrier.arrive.expect_tx.shared::cta.b64 _, [%0], %1;" ::"r"(bar), "r"(bytes) : "memory"); }
__device__ __forceinline__ void mbar_arrive(uint32_t bar) { asm volatile("mbarrier.arrive.shared::cta.b64 _, [%0];" ::"r"(bar) : "memory"); }
__device__ __forceinline__ uint32_t mapa(uint32_t addr, uint32_t cta) { uint32_t r; asm("mapa.shared::cluster.u32 %0, %1, %2;" : "=r"(r) : "r"(addr), "r"(cta)); return r; }
__device__ __forceinline__ void mbar_arrive_remote(uint32_t raddr) { asm volatile("mbarrier.arrive.shared::cluster.b64 _, [%0];" ::"r"(raddr) : "memory"); }
#define WAIT_LOOP(SEM) \
    "mov.u32 it, 0;\n" \
    "LOOP: mbarrier.try_wait.parity" SEM ".shared::cta.b64 p, [%0], %1;\n" \
    "@p bra DONE;\n" \
    "add.u32 it, it, 1;\n" \
    "setp.lt.u32 p, it, %2;\n" \
    "@p bra LOOP;\n" \
    "trap;\n" \
    "DONE: }"
__device__ __forceinline__ void mbar_wait(uint32_t bar, uint32_t parity) {
    asm volatile("{.reg .pred p; .reg .u32 it;\n" WAIT_LOOP("") ::"r"(bar), "r"(parity), "n"(SPIN_LIMIT) : "memory");
}
__device__ __forceinline__ void mbar_wait_cluster(uint32_t bar, uint32_t parity) {
    asm volatile("{.reg .pred p; .reg .u32 it;\n" WAIT_LOOP(".acquire.cluster") ::"r"(bar), "r"(parity), "n"(SPIN_LIMIT) : "memory");
}
__device__ __forceinline__ void mbar_test(uint32_t bar, uint32_t parity) {
    asm volatile("mbarrier.test_wait.parity.shared::cta.b64 pfull, [%0], %1;" ::"r"(bar), "r"(parity) : "memory");
}
__device__ __forceinline__ void mbar_check(uint32_t bar, uint32_t parity) {
    asm volatile("{.reg .pred p; .reg .u32 it;\n@pfull bra DONE;\n" WAIT_LOOP("") ::"r"(bar), "r"(parity), "n"(SPIN_LIMIT) : "memory");
}
__device__ __forceinline__ void mbar_arrive_lane0(uint32_t bar) { asm volatile("@plane0 mbarrier.arrive.shared::cta.b64 _, [%0];" ::"r"(bar) : "memory"); }
__device__ __forceinline__ void tma2d(uint32_t dst, const CUtensorMap* m, int c0, int c1, uint32_t bar) {
    asm volatile("cp.async.bulk.tensor.2d.shared::cluster.global.mbarrier::complete_tx::bytes [%0], [%1, {%3,%4}], [%2];" ::"r"(dst), "l"(m), "r"(bar), "r"(c0), "r"(c1) : "memory");
}
__device__ __forceinline__ void tma3d(uint32_t dst, const CUtensorMap* m, int c0, int c1, int c2, uint32_t bar) {
    asm volatile("cp.async.bulk.tensor.3d.shared::cluster.global.mbarrier::complete_tx::bytes [%0], [%1, {%3,%4,%5}], [%2];" ::"r"(dst), "l"(m), "r"(bar), "r"(c0), "r"(c1), "r"(c2) : "memory");
}
__device__ __forceinline__ void tma_store2d(const CUtensorMap* m, int c0, int c1, uint32_t src) {
    asm volatile("cp.async.bulk.tensor.2d.global.shared::cta.bulk_group [%0, {%2,%3}], [%1];" ::"l"(m), "r"(src), "r"(c0), "r"(c1) : "memory");
}
__device__ __forceinline__ void tma_red2d(const CUtensorMap* m, int c0, int c1, uint32_t src) {
    asm volatile("cp.reduce.async.bulk.tensor.2d.global.shared::cta.add.bulk_group [%0, {%2,%3}], [%1];" ::"l"(m), "r"(src), "r"(c0), "r"(c1) : "memory");
}
__device__ __forceinline__ void bulk_s2c(uint32_t rdst, uint32_t src, uint32_t bytes, uint32_t rbar) {
    asm volatile("cp.async.bulk.shared::cluster.shared::cta.mbarrier::complete_tx::bytes [%0], [%1], %2, [%3];" ::"r"(rdst), "r"(src), "r"(bytes), "r"(rbar) : "memory");
}
__device__ __forceinline__ void fence_async_smem() { asm volatile("fence.proxy.async.shared::cta;" ::: "memory"); }
__device__ __forceinline__ void fence_async_all() { asm volatile("fence.proxy.async;" ::: "memory"); }
__device__ __forceinline__ void bar_sync(int id, int n) { asm volatile("bar.sync %0, %1;" ::"r"(id), "r"(n) : "memory"); }
__device__ __forceinline__ void bar_arrive(int id, int n) { asm volatile("bar.arrive %0, %1;" ::"r"(id), "r"(n) : "memory"); }
__device__ __forceinline__ void ldsm4(uint32_t& a, uint32_t& b, uint32_t& c, uint32_t& d, uint32_t addr) {
    asm volatile("ldmatrix.sync.aligned.m8n8.x4.shared.b16 {%0,%1,%2,%3}, [%4];" : "=r"(a), "=r"(b), "=r"(c), "=r"(d) : "r"(addr) : "memory");
}
__device__ __forceinline__ void stsm4(uint32_t addr, uint32_t a, uint32_t b, uint32_t c, uint32_t d) {
    asm volatile("stmatrix.sync.aligned.m8n8.x4.shared.b16 [%0], {%1,%2,%3,%4};" ::"r"(addr), "r"(a), "r"(b), "r"(c), "r"(d) : "memory");
}
__device__ __forceinline__ void lds4(uint32_t* a, uint32_t addr) {
    asm volatile("ld.shared.v4.u32 {%0,%1,%2,%3}, [%4];" : "=r"(a[0]), "=r"(a[1]), "=r"(a[2]), "=r"(a[3]) : "r"(addr) : "memory");
}
__device__ __forceinline__ void lds4f(float* a, uint32_t addr) {
    asm volatile("ld.shared.v4.f32 {%0,%1,%2,%3}, [%4];" : "=f"(a[0]), "=f"(a[1]), "=f"(a[2]), "=f"(a[3]) : "r"(addr) : "memory");
}
__device__ __forceinline__ void sts4(uint32_t addr, uint32_t a, uint32_t b, uint32_t c, uint32_t d) {
    asm volatile("st.shared.v4.u32 [%0], {%1,%2,%3,%4};" ::"r"(addr), "r"(a), "r"(b), "r"(c), "r"(d) : "memory");
}
__device__ __forceinline__ void red4(float* p, const float* v) {
    asm volatile("red.relaxed.gpu.global.add.v4.f32 [%0], {%1,%2,%3,%4};" ::"l"(p), "f"(v[0]), "f"(v[1]), "f"(v[2]), "f"(v[3]) : "memory");
}
__device__ __forceinline__ uint32_t pack2(float lo, float hi) {
    uint32_t r;
    asm("cvt.rn.bf16x2.f32 %0, %1, %2;" : "=r"(r) : "f"(hi), "f"(lo));
    return r;
}
__device__ __forceinline__ void mma16816(float (&c)[4], uint32_t a0, uint32_t a1, uint32_t a2, uint32_t a3, uint32_t b0, uint32_t b1) {
    asm("mma.sync.aligned.m16n8k16.row.col.f32.bf16.bf16.f32 {%0,%1,%2,%3}, {%4,%5,%6,%7}, {%8,%9}, {%0,%1,%2,%3};"
        : "+f"(c[0]), "+f"(c[1]), "+f"(c[2]), "+f"(c[3]) : "r"(a0), "r"(a1), "r"(a2), "r"(a3), "r"(b0), "r"(b1));
}
__device__ __forceinline__ float ex2f(float x) { float y; asm("ex2.approx.ftz.f32 %0, %1;" : "=f"(y) : "f"(x)); return y; }
__device__ __forceinline__ float rcpf(float x) { float y; asm("rcp.approx.ftz.f32 %0, %1;" : "=f"(y) : "f"(x)); return y; }
__device__ __forceinline__ void wg_fence() { asm volatile("wgmma.fence.sync.aligned;" ::: "memory"); }
__device__ __forceinline__ void wg_commit() { asm volatile("wgmma.commit_group.sync.aligned;" ::: "memory"); }
template <int N> __device__ __forceinline__ void wg_wait() { asm volatile("wgmma.wait_group.sync.aligned %0;" ::"n"(N) : "memory"); }
__device__ __forceinline__ uint32_t desc_lo(uint32_t addr) { return (addr & 0x3FFFFu) >> 4; }

template <int N, bool ACC, int STEP> __device__ __forceinline__ void wgmma_rs(float (&d)[32], const uint32_t* a, uint64_t& db) {
    if constexpr (N == 64 && ACC) {
        asm volatile("{.reg .pred p; setp.ne.b32 p, 1, 0;\n"
            "wgmma.mma_async.sync.aligned.m64n64k16.f32.bf16.bf16 {%0,%1,%2,%3,%4,%5,%6,%7,%8,%9,%10,%11,%12,%13,%14,%15,%16,%17,%18,%19,%20,%21,%22,%23,%24,%25,%26,%27,%28,%29,%30,%31}, {%33,%34,%35,%36}, %32, p, 1, 1, 1;\n"
            "add.s64 %32, %32, %37;}\n"
            : "+f"(d[0]), "+f"(d[1]), "+f"(d[2]), "+f"(d[3]), "+f"(d[4]), "+f"(d[5]), "+f"(d[6]), "+f"(d[7]), "+f"(d[8]), "+f"(d[9]), "+f"(d[10]), "+f"(d[11]),
              "+f"(d[12]), "+f"(d[13]), "+f"(d[14]), "+f"(d[15]), "+f"(d[16]), "+f"(d[17]), "+f"(d[18]), "+f"(d[19]), "+f"(d[20]), "+f"(d[21]), "+f"(d[22]), "+f"(d[23]),
              "+f"(d[24]), "+f"(d[25]), "+f"(d[26]), "+f"(d[27]), "+f"(d[28]), "+f"(d[29]), "+f"(d[30]), "+f"(d[31]), "+l"(db)
            : "r"(a[0]), "r"(a[1]), "r"(a[2]), "r"(a[3]), "n"(STEP));
    } else if constexpr (N == 64) {
        asm volatile("{.reg .pred p; setp.ne.b32 p, 0, 0;\n"
            "wgmma.mma_async.sync.aligned.m64n64k16.f32.bf16.bf16 {%0,%1,%2,%3,%4,%5,%6,%7,%8,%9,%10,%11,%12,%13,%14,%15,%16,%17,%18,%19,%20,%21,%22,%23,%24,%25,%26,%27,%28,%29,%30,%31}, {%33,%34,%35,%36}, %32, p, 1, 1, 1;\n"
            "add.s64 %32, %32, %37;}\n"
            : "=f"(d[0]), "=f"(d[1]), "=f"(d[2]), "=f"(d[3]), "=f"(d[4]), "=f"(d[5]), "=f"(d[6]), "=f"(d[7]), "=f"(d[8]), "=f"(d[9]), "=f"(d[10]), "=f"(d[11]),
              "=f"(d[12]), "=f"(d[13]), "=f"(d[14]), "=f"(d[15]), "=f"(d[16]), "=f"(d[17]), "=f"(d[18]), "=f"(d[19]), "=f"(d[20]), "=f"(d[21]), "=f"(d[22]), "=f"(d[23]),
              "=f"(d[24]), "=f"(d[25]), "=f"(d[26]), "=f"(d[27]), "=f"(d[28]), "=f"(d[29]), "=f"(d[30]), "=f"(d[31]), "+l"(db)
            : "r"(a[0]), "r"(a[1]), "r"(a[2]), "r"(a[3]), "n"(STEP));
    } else {
        static_assert(N == 48 && ACC, "unsupported shape");
        asm volatile("{.reg .pred p; setp.ne.b32 p, 1, 0;\n"
            "wgmma.mma_async.sync.aligned.m64n48k16.f32.bf16.bf16 {%0,%1,%2,%3,%4,%5,%6,%7,%8,%9,%10,%11,%12,%13,%14,%15,%16,%17,%18,%19,%20,%21,%22,%23}, {%25,%26,%27,%28}, %24, p, 1, 1, 1;\n"
            "add.s64 %24, %24, %29;}\n"
            : "+f"(d[0]), "+f"(d[1]), "+f"(d[2]), "+f"(d[3]), "+f"(d[4]), "+f"(d[5]), "+f"(d[6]), "+f"(d[7]), "+f"(d[8]), "+f"(d[9]), "+f"(d[10]), "+f"(d[11]),
              "+f"(d[12]), "+f"(d[13]), "+f"(d[14]), "+f"(d[15]), "+f"(d[16]), "+f"(d[17]), "+f"(d[18]), "+f"(d[19]), "+f"(d[20]), "+f"(d[21]), "+f"(d[22]), "+f"(d[23]), "+l"(db)
            : "r"(a[0]), "r"(a[1]), "r"(a[2]), "r"(a[3]), "n"(STEP));
    }
}
template <bool ACC> __device__ __forceinline__ void wgmma_ss72t(float (&d)[36], uint32_t alo, uint32_t blo) {
    if constexpr (ACC) {
        asm volatile("{.reg .pred p; .reg .b64 da, db; setp.ne.b32 p, 1, 0; mov.b64 da, {%36, 0x40000040}; mov.b64 db, {%37, 0x40000040};\n"
            "wgmma.mma_async.sync.aligned.m64n72k16.f32.bf16.bf16 {%0,%1,%2,%3,%4,%5,%6,%7,%8,%9,%10,%11,%12,%13,%14,%15,%16,%17,%18,%19,%20,%21,%22,%23,%24,%25,%26,%27,%28,%29,%30,%31,%32,%33,%34,%35}, da, db, p, 1, 1, 1, 1;}\n"
            : "+f"(d[0]), "+f"(d[1]), "+f"(d[2]), "+f"(d[3]), "+f"(d[4]), "+f"(d[5]), "+f"(d[6]), "+f"(d[7]), "+f"(d[8]), "+f"(d[9]), "+f"(d[10]), "+f"(d[11]),
              "+f"(d[12]), "+f"(d[13]), "+f"(d[14]), "+f"(d[15]), "+f"(d[16]), "+f"(d[17]), "+f"(d[18]), "+f"(d[19]), "+f"(d[20]), "+f"(d[21]), "+f"(d[22]), "+f"(d[23]),
              "+f"(d[24]), "+f"(d[25]), "+f"(d[26]), "+f"(d[27]), "+f"(d[28]), "+f"(d[29]), "+f"(d[30]), "+f"(d[31]), "+f"(d[32]), "+f"(d[33]), "+f"(d[34]), "+f"(d[35])
            : "r"(alo), "r"(blo));
    } else {
        asm volatile("{.reg .pred p; .reg .b64 da, db; setp.ne.b32 p, 0, 0; mov.b64 da, {%36, 0x40000040}; mov.b64 db, {%37, 0x40000040};\n"
            "wgmma.mma_async.sync.aligned.m64n72k16.f32.bf16.bf16 {%0,%1,%2,%3,%4,%5,%6,%7,%8,%9,%10,%11,%12,%13,%14,%15,%16,%17,%18,%19,%20,%21,%22,%23,%24,%25,%26,%27,%28,%29,%30,%31,%32,%33,%34,%35}, da, db, p, 1, 1, 1, 1;}\n"
            : "=f"(d[0]), "=f"(d[1]), "=f"(d[2]), "=f"(d[3]), "=f"(d[4]), "=f"(d[5]), "=f"(d[6]), "=f"(d[7]), "=f"(d[8]), "=f"(d[9]), "=f"(d[10]), "=f"(d[11]),
              "=f"(d[12]), "=f"(d[13]), "=f"(d[14]), "=f"(d[15]), "=f"(d[16]), "=f"(d[17]), "=f"(d[18]), "=f"(d[19]), "=f"(d[20]), "=f"(d[21]), "=f"(d[22]), "=f"(d[23]),
              "=f"(d[24]), "=f"(d[25]), "=f"(d[26]), "=f"(d[27]), "=f"(d[28]), "=f"(d[29]), "=f"(d[30]), "=f"(d[31]), "=f"(d[32]), "=f"(d[33]), "=f"(d[34]), "=f"(d[35])
            : "r"(alo), "r"(blo));
    }
}
__device__ __forceinline__ void wgmma_ss24(float (&d)[12], uint32_t alo, uint32_t blo) {
        asm volatile("{.reg .pred p; .reg .b64 da, db; setp.ne.b32 p, 0, 0; mov.b64 da, {%12, 0x40000040}; mov.b64 db, {%13, 0x40000040};\n"
            "wgmma.mma_async.sync.aligned.m64n24k16.f32.bf16.bf16 {%0,%1,%2,%3,%4,%5,%6,%7,%8,%9,%10,%11}, da, db, p, 1, 1, 0, 1;}\n"
            : "=f"(d[0]), "=f"(d[1]), "=f"(d[2]), "=f"(d[3]), "=f"(d[4]), "=f"(d[5]), "=f"(d[6]), "=f"(d[7]), "=f"(d[8]), "=f"(d[9]), "=f"(d[10]), "=f"(d[11])
            : "r"(alo), "r"(blo));
}

__host__ __device__ constexpr uint32_t full_bar(int g) { return B_FULL + (g % NSTG) * 8; }
__host__ __device__ constexpr uint32_t empty_bar(int g) { return B_EMPTY + ((g + NSTG) % NSTG) * 8; }
__host__ __device__ constexpr uint32_t full_par(int g) { return (g / NSTG) & 1; }

struct NoHook { __device__ __forceinline__ void operator()(int) const {} };

template <int N, int G, int K0, int NK, int POS, bool ZERO, class Hook = NoHook>
__device__ __forceinline__ void mma_stage(float (&d)[32], const uint32_t (&A)[128], uint32_t sb, uint64_t& db, int next_wg, Hook hook = Hook()) {
#pragma unroll
    for (int k = 0; k < NK; ++k) {
        constexpr int LAST = (((G + 1) % NSTG) - (G % NSTG)) * (STG_BYTES >> 4) - (NK - 1) * 128;
        if (ZERO && k == 0) wgmma_rs<64, false, 128>(d, &A[(K0 + k) * 4], db);
        else if (k == NK - 1) wgmma_rs<N, true, LAST>(d, &A[(K0 + k) * 4], db);
        else wgmma_rs<N, true, 128>(d, &A[(K0 + k) * 4], db);
        hook(k);
        if (k == NK - 3) {
            if (POS == 2 && next_wg) bar_arrive(next_wg, 256);
            if (POS != 0) {
                wg_commit();
                wg_wait<1>();
                mbar_arrive_lane0(sb + empty_bar(G - 1));
            }
        }
        if (k == NK - 2 && POS != 2) mbar_test(sb + full_bar(G + 1), full_par(G + 1));
    }
    wg_commit();
    if (POS != 2) mbar_check(sb + full_bar(G + 1), full_par(G + 1));
}
template <int G> __device__ __forceinline__ void chunk_begin(const Maps& maps, uint64_t& db, uint32_t sb, int g) {
    db = maps.desc[G / 4] + desc_lo(sb + SM_RING);
    mbar_wait(sb + full_bar(G), full_par(G));
    bar_sync(1 + g, 256);
    wg_fence();
}
template <int G> __device__ __forceinline__ void chunk_end(uint32_t sb) {
    wg_wait<0>();
    mbar_arrive_lane0(sb + empty_bar(G));
}
template <int N, int C, bool ZERO>
__device__ __forceinline__ void g1_mma(float (&d)[32], const uint32_t (&A)[128], uint32_t sb, uint64_t& db, int next_wg) {
    mma_stage<N, 4 * C, 0, 8, 0, ZERO>(d, A, sb, db, next_wg);
    mma_stage<N, 4 * C + 1, 8, 8, 1, false>(d, A, sb, db, next_wg);
    mma_stage<N, 4 * C + 2, 16, 8, 1, false>(d, A, sb, db, next_wg);
    mma_stage<N, 4 * C + 3, 24, 8, 2, false>(d, A, sb, db, next_wg);
}

__device__ __forceinline__ uint32_t phi2(float a, float b) {
    uint32_t r = pack2(fmaxf(fmaf(a, LN2, 1.f), ex2f(-fabsf(a))), fmaxf(fmaf(b, LN2, 1.f), ex2f(-fabsf(b))));
    asm("add.rn.bf16x2 %0, %0, %1;" : "+r"(r) : "r"(0x35863586u));
    return r;
}
__device__ __forceinline__ float mish(float t) {
    const float e = ex2f(t);
    return fmaf(t, rcpf(fmaf(e, fmaf(e, -0.5f, -1.f), -1.f)), t);
}
__device__ __forceinline__ void phi_tile(const float (&d)[32], uint32_t tile) {
#pragma unroll
    for (int u = 0; u < 4; ++u)
        stsm4(tile ^ (u << 5), phi2(d[8 * u], d[8 * u + 1]), phi2(d[8 * u + 2], d[8 * u + 3]), phi2(d[8 * u + 4], d[8 * u + 5]), phi2(d[8 * u + 6], d[8 * u + 7]));
}
template <int NU> __device__ __forceinline__ void load_bias(float (&d)[32], uint32_t addr) {
#pragma unroll
    for (int i = 0; i < 2 * NU; ++i) lds4f(&d[4 * i], addr + i * 64);
}

__global__ void __cluster_dims__(2, 1, 1) __launch_bounds__(384, 1)
fused_kernel(const __grid_constant__ Maps maps, const __nv_bfloat16* __restrict__ b1) {
    extern __shared__ uint8_t smem_raw[];
    const uint32_t sb = (smem_u32(smem_raw) + 1023u) & ~1023u;
    const int warp = __shfl_sync(0xffffffffu, (int)(threadIdx.x >> 5), 0);
    const int lane = threadIdx.x & 31;
    const int rank = blockIdx.x & 1;
    int mi, pr;
    {
        const int c = blockIdx.x >> 1;
        int g, m;
        if (c < 4) { g = 15; m = c; }
        else if (c < 36) { g = (c - 4) & 7; m = (c - 4) >> 3; }
        else { m = ((c - 36) * 37) >> 8; g = 8 + (c - 36) - 7 * m; }
        mi = (g & ~1) | (m & 1);
        pr = (g & 1) * 2 + (m >> 1);
    }
    const int j = pr * 2 + rank;
    const int row0 = mi * 128;
    const uint32_t swz = (lane & 15) * 128 + (((lane >> 4) ^ (lane & 7)) << 4);

    if (warp >= 8) {
        asm volatile("setmaxnreg.dec.sync.aligned.u32 56;");
        if (warp == 8) {
            if (lane == 0) {
#pragma unroll
                for (int i = 0; i < 8; ++i) mbar_init(sb + B_XFULL + i * 8, 1);
#pragma unroll
                for (int i = 0; i < NSTG; ++i) mbar_init(sb + B_FULL + i * 8, 1);
                fence_async_smem();
            }
            __syncwarp();
            bar_arrive(3, 384);
            asm volatile("barrier.cluster.arrive.relaxed.aligned;" ::: "memory");
            TSH(16);
            if (lane == 0) {
#pragma unroll
                for (int i = 0; i < 8; ++i) {
                    const int b = (i & 1) * 4 + (i >> 1);
                    mbar_expect_tx(sb + B_XFULL + b * 8, 16384);
                    tma3d(sb + SM_XA + b * 16384, &maps.x, 0, row0 + (b >> 2) * 64, (b & 3) * 2, sb + B_XFULL + b * 8);
                }
                TSH(17);
#pragma unroll
                for (int i = 0; i < NSTG; ++i) mbar_init(sb + B_EMPTY + i * 8, 8);
                uint32_t slot = 0, phase = 1;
#pragma unroll 1
                for (int g = 0; g < 40; ++g) {
                    const int s = g & 3, c = g >> 2;
                    const uint32_t dst = sb + SM_RING + slot * STG_BYTES, bar = sb + B_FULL + slot * 8;
                    if (g >= NSTG) mbar_wait(sb + B_EMPTY + slot * 8, phase);
                    if (c < 6) {
                        mbar_expect_tx(bar, STG_BYTES);
                        if (c >= 3) tma2d(dst, &maps.w1, 176 * j + 64 * (c - 3), s * 128, bar);
                        else tma2d(dst, &maps.wqkv, 64 * j + (c == 2 ? 0 : 512 * (c + 1)), s * 128, bar);
                    } else {
                        const int col = 256 * rank + 64 * (c - 6), jj = j ^ (s & 1);
                        if (s < 2) {
                            mbar_expect_tx(bar, STG_BYTES);
                            tma2d(dst, &maps.w2, col, 176 * jj, bar);
                        } else {
                            mbar_expect_tx(bar, 112 * 128);
                            tma2d(dst, &maps.wo, col, 64 * jj, bar);
                            tma2d(dst + 8192, &maps.w2b, col, 176 * jj + 128, bar);
                        }
                    }
                    if (++slot == NSTG) { slot = 0; phase ^= 1; }
                }
            }
            __syncwarp();
            asm volatile("barrier.cluster.wait.aligned;" ::: "memory");
            if (lane == 0) mbar_wait_cluster(sb + B_DONE, 0);
        } else if (warp == 11) {
            const unsigned epoch = *(volatile unsigned*)&g_count >> 7;
            bar_arrive(3, 384);
#pragma unroll
            for (int f = 0; f < 3; ++f) {
                const int col = 64 * f + 2 * lane;
                float lo = 0.f, hi = 0.f;
                if (col < 176 && 176 * j + col < F_) {
                    const uint32_t v = *(const uint32_t*)(b1 + 176 * j + col);
                    lo = __uint_as_float(v << 16) * LOG2E;
                    hi = __uint_as_float(v & 0xffff0000u) * LOG2E;
                }
                sts4(sb + SM_BIAS + f * 512 + lane * 16, __float_as_uint(lo), __float_as_uint(hi), __float_as_uint(lo), __float_as_uint(hi));
            }
            if (lane == 0) asm volatile("st.shared.u32 [%0], %1;" ::"r"(sb + SM_KVOFF), "r"(((epoch & 1) * 8 + j) * (KV_FLOATS * 4)) : "memory");
            if (lane < 17) *(float4*)&g_kv[(epoch & 1) ^ 1][j][mi * 68 + lane * 4] = make_float4(0.f, 0.f, 0.f, 0.f);
            asm volatile("barrier.cluster.arrive.release.aligned; barrier.cluster.wait.aligned;" ::: "memory");
        } else {
            const int hw = warp - 9;
            const unsigned epoch = *(volatile unsigned*)&g_count >> 7;
            if (lane == 0) {
                if (hw == 0) {
#pragma unroll
                    for (int i = 0; i < 8; ++i) { mbar_init(sb + B_PF + i * 8, 1); mbar_init(sb + B_PO + i * 8, 1); }
#pragma unroll
                    for (int i = 0; i < 8; ++i) { mbar_expect_tx(sb + B_PF + i * 8, 4096); mbar_expect_tx(sb + B_PO + i * 8, 3584); }
                } else {
                    mbar_init(sb + B_KVST, 8);
                    mbar_init(sb + B_KVRDY, 2);
                    mbar_init(sb + B_DONE, 8);
                }
                asm volatile("fence.mbarrier_init.release.cluster;" ::: "memory");
            }
            __syncwarp();
            bar_sync(3, 384);
            if (hw == 0 && lane == 0) {
                mbar_wait(sb + B_XFULL + (j >> 1) * 8, 0);
                tma_store2d(&maps.oinit, 64 * j, row0, sb + SM_XA + j * 8192);
                mbar_wait(sb + B_XFULL + (4 + (j >> 1)) * 8, 0);
                tma_store2d(&maps.oinit, 64 * j, row0 + 64, sb + SM_XA + 65536 + j * 8192);
                asm volatile("cp.async.bulk.commit_group; cp.async.bulk.wait_group.read 0;" ::: "memory");
            }
            __syncwarp();
            TSH(hw * 8 + 0);
            asm volatile("barrier.cluster.arrive.relaxed.aligned; barrier.cluster.wait.aligned;" ::: "memory");
            if (lane == 0) {
                if (hw == 0) {
                    asm volatile("cp.async.bulk.wait_group 0;" ::: "memory");
                    fence_async_all();
                    mbar_wait(sb + B_KVST, 0);
                    TSH(1);
                    asm volatile("fence.acq_rel.gpu; red.relaxed.gpu.global.add.u32 [%0], 1;" ::"l"(&g_count) : "memory");
                    TSH(2);
                } else {
                    mbar_wait(sb + B_KVST, 0);
                }
                const unsigned target = (epoch + 1) << 7;
                for (int it = 0;; ++it) {
                    unsigned v;
                    asm volatile("ld.acquire.gpu.global.u32 %0, [%1];" : "=r"(v) : "l"(&g_count) : "memory");
                    if ((int)(v - target) >= 0) break;
                    if (it > SPIN_LIMIT) asm volatile("trap;");
                }
            }
            __syncwarp();
            TSH(hw * 8 + 3);
            const float* gk = &g_kv[epoch & 1][j][hw * 2 * 272];
#pragma unroll
            for (int h = 0; h < 2; ++h) {
                const float4 t0 = __ldcg((const float4*)(gk + h * 272 + lane * 4));
                const float4 t1 = __ldcg((const float4*)(gk + h * 272 + 128 + lane * 4));
                const float z = __ldcg(gk + h * 272 + 256 + (lane & 15));
                const uint32_t base = sb + X_KVB + hw * 2048;
                stsm4(base + (swz ^ (h << 6)), pack2(t0.x, t0.y), pack2(t0.z, t0.w), pack2(t1.x, t1.y), pack2(t1.z, t1.w));
                const uint32_t zz = pack2(z, z);
                if (lane < 16) sts4(base + lane * 128 + (((h * 4 + 2) ^ (lane & 7)) << 4), zz, zz, zz, zz);
            }
            fence_async_all();
            __syncwarp();
            if (lane == 0) mbar_arrive(sb + B_KVRDY);
            TSH(hw * 8 + 4);
        }
    } else {
        asm volatile("setmaxnreg.inc.sync.aligned.u32 224;");
        asm volatile(".reg .pred pfull, plane0; setp.eq.u32 plane0, %0, 0;" ::"r"(lane));
        const int g = warp >> 2, wl = warp & 3;
        uint32_t A[128];
        float d[32];
        bar_sync(3, 384);
        {
            float st[4][4];
#pragma unroll
            for (int i = 0; i < 4; ++i)
#pragma unroll
                for (int k = 0; k < 4; ++k) st[i][k] = 0.f;
            const uint32_t xb = sb + SM_XA + g * 65536 + wl * 2048;
#pragma unroll
            for (int e = 0; e < 4; ++e) {
                mbar_wait(sb + B_XFULL + (g * 4 + e) * 8, 0);
                TS(g, e);
#pragma unroll
                for (int t = 0; t < 8; ++t) {
                    const int s = e * 8 + t;
                    ldsm4(A[4 * s], A[4 * s + 1], A[4 * s + 2], A[4 * s + 3], xb + (s >> 2) * 8192 + (swz ^ ((s & 3) << 5)));
                }
#pragma unroll
                for (int t = 0; t < 8; ++t) {
                    const int s = e * 8 + t;
                    mma16816(st[(t & 1) * 2], A[4 * s], ONES2, A[4 * s + 2], ONES2, A[4 * s], A[4 * s + 2]);
                    mma16816(st[(t & 1) * 2 + 1], A[4 * s + 1], ONES2, A[4 * s + 3], ONES2, A[4 * s + 1], A[4 * s + 3]);
                }
            }
            const int r = lane >> 2;
            const int src = 4 * r + (r >> 1);
            const bool odd = r & 1;
            const float q0 = __shfl_sync(0xffffffffu, odd ? st[0][1] + st[2][1] : st[0][0] + st[2][0], src);
            const float s0 = __shfl_sync(0xffffffffu, odd ? st[0][3] + st[2][3] : st[0][2] + st[2][2], src);
            const float q1 = __shfl_sync(0xffffffffu, odd ? st[1][1] + st[3][1] : st[1][0] + st[3][0], src);
            const float s1 = __shfl_sync(0xffffffffu, odd ? st[1][3] + st[3][3] : st[1][2] + st[3][2], src);
            if (g == 1) bar_arrive(1, 256);
            asm volatile("barrier.cluster.arrive.relaxed.aligned;" ::: "memory");
            const float m0 = s0 * (1.f / D_), m1 = s1 * (1.f / D_);
            const uint32_t rr = pack2(LOG2E * rsqrtf(fmaxf(fmaf(q0, 1.f / D_, -m0 * m0), 0.f) + 1e-5f), LOG2E * rsqrtf(fmaxf(fmaf(q1, 1.f / D_, -m1 * m1), 0.f) + 1e-5f));
            const float c0 = -m0 * __uint_as_float(rr << 16), c1 = -m1 * __uint_as_float(rr & 0xffff0000u);
            const uint32_t r0 = __byte_perm(rr, 0, 0x1010), r1 = __byte_perm(rr, 0, 0x3232), cc0 = pack2(c0, c0), cc1 = pack2(c1, c1);
#pragma unroll
            for (int i = 0; i < 128; ++i) asm("fma.rn.bf16x2 %0, %0, %1, %2;" : "+r"(A[i]) : "r"((i & 1) ? r1 : r0), "r"((i & 1) ? cc1 : cc0));
        }
        TS(g, 4);
        uint64_t db;
        const uint32_t tile = sb + X_PK + g * 16384 + wl * 2048;
        const uint32_t bias = sb + SM_BIAS + (lane & 3) * 16;
        const uint32_t peer = mapa(sb, rank ^ 1);
        const int nw = 2 - g;
        chunk_begin<0>(maps, db, sb, g);
        TS(g, 8);
        g1_mma<64, 0, true>(d, A, sb, db, nw);
        chunk_end<3>(sb);
        TS(g, 9);
        asm volatile("barrier.cluster.wait.aligned;" ::: "memory");
        phi_tile(d, tile + swz);
        TS(g, 10);
        chunk_begin<4>(maps, db, sb, g);
        g1_mma<64, 1, true>(d, A, sb, db, nw);
        chunk_end<7>(sb);
        TS(g, 12);
#pragma unroll
        for (int u = 0; u < 4; ++u)
            stsm4((tile + 8192 + swz) ^ (u << 5), pack2(d[8 * u], d[8 * u + 1]), pack2(d[8 * u + 2], d[8 * u + 3]), pack2(d[8 * u + 4], d[8 * u + 5]), pack2(d[8 * u + 6], d[8 * u + 7]));
        sts4(sb + X_KVB + wl * 512 + lane * 16, ONES2, ONES2, ONES2, ONES2);
        fence_async_smem();
        TS(g, 13);
        {
            float kv[36];
            const uint32_t pk_lo = desc_lo(sb + X_PK + g * 16384);
            const uint32_t v_lo = pk_lo + 512 + ((1536 - g * 1024) << 16);
            chunk_begin<8>(maps, db, sb, g);
            wgmma_ss72t<false>(kv, pk_lo, v_lo);
#pragma unroll
            for (int k = 1; k < 4; ++k) wgmma_ss72t<true>(kv, pk_lo + k * 128, v_lo + k * (128 - (128 << 16)));
            g1_mma<64, 2, true>(d, A, sb, db, nw);
            chunk_end<11>(sb);
            TS(g, 15);
            uint32_t off;
            asm volatile("ld.shared.u32 %0, [%1];" : "=r"(off) : "r"(sb + SM_KVOFF) : "memory");
            float* gk = (float*)((char*)&g_kv[0][0][0] + off) + wl * 272;
            if (wl == 0) { red4(gk + lane * 4, &kv[0]); red4(gk + 128 + lane * 4, &kv[4]); }
            else if (wl == 1) { red4(gk + lane * 4, &kv[8]); red4(gk + 128 + lane * 4, &kv[12]); }
            else if (wl == 2) { red4(gk + lane * 4, &kv[16]); red4(gk + 128 + lane * 4, &kv[20]); }
            else { red4(gk + lane * 4, &kv[24]); red4(gk + 128 + lane * 4, &kv[28]); }
            if ((lane & 2) == 0) asm volatile("red.relaxed.gpu.global.add.f32 [%0], %1;" ::"l"(gk + 256 + (lane >> 2) + (lane & 1) * 8), "f"((lane & 1) ? kv[34] : kv[32]) : "memory");
            __syncwarp();
            mbar_arrive_lane0(sb + B_KVST);
        }
        bar_sync(4 + g, 128);
        phi_tile(d, tile + swz);
        fence_async_smem();
        load_bias<4>(d, bias);
        TS(g, 16);
        const uint32_t own = sb + X_OWN + warp * 4096;
#pragma unroll
        for (int f = 0; f < 2; ++f) {
            if (f == 0) { chunk_begin<12>(maps, db, sb, g); g1_mma<64, 3, false>(d, A, sb, db, nw); chunk_end<15>(sb); }
            else { chunk_begin<16>(maps, db, sb, g); g1_mma<64, 4, false>(d, A, sb, db, nw); chunk_end<19>(sb); }
            TS(g, 18 + 3 * f);
#pragma unroll
            for (int u = 0; u < 4; ++u)
                sts4(own + f * 2048 + u * 512 + lane * 16, pack2(mish(d[8 * u]), mish(d[8 * u + 1])), pack2(mish(d[8 * u + 2]), mish(d[8 * u + 3])),
                     pack2(mish(d[8 * u + 4]), mish(d[8 * u + 5])), pack2(mish(d[8 * u + 6]), mish(d[8 * u + 7])));
            fence_async_smem();
            __syncwarp();
            if (lane == 0) bulk_s2c(peer + X_PF + warp * 4096 + f * 2048, own + f * 2048, 2048, peer + B_PF + warp * 8);
            if (f == 0) load_bias<4>(d, bias + 512);
            else load_bias<3>(d, bias + 1024);
            TS(g, 19 + 3 * f);
        }
        {
            float o[4][12];
            const uint32_t pq_lo = desc_lo(sb + X_PK + g * 16384) | (1u << 16);
            const uint32_t kv_lo = desc_lo(sb + X_KVB) | (1u << 16);
            chunk_begin<20>(maps, db, sb, g);
            mma_stage<48, 20, 0, 8, 0, false>(d, A, sb, db, nw);
            mma_stage<48, 21, 8, 8, 1, false>(d, A, sb, db, nw);
            mma_stage<48, 22, 16, 8, 1, false>(d, A, sb, db, nw);
            mma_stage<48, 23, 24, 8, 2, false>(d, A, sb, db, 0);
            mbar_wait(sb + B_KVRDY, 0);
#pragma unroll
            for (int h = 0; h < 4; ++h) {
                wgmma_ss24(o[h], pq_lo + h * 2, kv_lo + (h >> 1) * 128 + (h & 1) * 4);
                if (h == 1) bar_arrive(nw, 256);
            }
            wg_commit();
            chunk_end<23>(sb);
            TS(g, 24);
#pragma unroll
            for (int h = 0; h < 4; ++h) {
                const float i0 = rcpf(o[h][8] + 1e-6f), i1 = rcpf(o[h][10] + 1e-6f);
                uint32_t* a = &A[64 + 4 * h];
                a[0] = pack2(o[h][0] * i0, o[h][1] * i0);
                a[1] = pack2(o[h][2] * i1, o[h][3] * i1);
                a[2] = pack2(o[h][4] * i0, o[h][5] * i0);
                a[3] = pack2(o[h][6] * i1, o[h][7] * i1);
                sts4(tile + h * 512 + lane * 16, a[0], a[1], a[2], a[3]);
            }
            fence_async_smem();
            __syncwarp();
            if (lane == 0) bulk_s2c(peer + X_PL + warp * 3584, tile, 2048, peer + B_PO + warp * 8);
#pragma unroll
            for (int u = 0; u < 3; ++u) {
                uint32_t* a = &A[80 + 4 * u];
#pragma unroll
                for (int i = 0; i < 4; ++i) a[i] = pack2(mish(d[8 * u + 2 * i]), mish(d[8 * u + 2 * i + 1]));
                sts4(tile + 8192 + u * 512 + lane * 16, a[0], a[1], a[2], a[3]);
            }
            fence_async_smem();
            __syncwarp();
            if (lane == 0) bulk_s2c(peer + X_PL + warp * 3584 + 2048, tile + 8192, 1536, peer + B_PO + warp * 8);
#pragma unroll
            for (int s = 0; s < 8; ++s) lds4(&A[4 * s], own + s * 512 + lane * 16);
            mbar_wait_cluster(sb + B_PF + warp * 8, 0);
#pragma unroll
            for (int s = 0; s < 8; ++s) lds4(&A[32 + 4 * s], sb + X_PF + warp * 4096 + s * 512 + lane * 16);
        }
        TS(g, 25);
        auto g2_store = [&](int c) {
            const uint32_t stg = sb + X_PF + warp * 4096 + (c & 1) * 2048;
            if (c >= 2) {
                if (lane == 0) asm volatile("cp.async.bulk.wait_group.read 1;" ::: "memory");
                __syncwarp();
            }
#pragma unroll
            for (int u = 0; u < 4; ++u)
                stsm4((stg + swz) ^ (u << 5), pack2(d[8 * u] * LN2, d[8 * u + 1] * LN2), pack2(d[8 * u + 2] * LN2, d[8 * u + 3] * LN2),
                      pack2(d[8 * u + 4] * LN2, d[8 * u + 5] * LN2), pack2(d[8 * u + 6] * LN2, d[8 * u + 7] * LN2));
            fence_async_smem();
            __syncwarp();
            if (lane == 0) {
                tma_red2d(&maps.ored, 256 * rank + 64 * c, row0 + warp * 16, stg);
                asm volatile("cp.async.bulk.commit_group;" ::: "memory");
            }
        };
        chunk_begin<24>(maps, db, sb, g);
        mma_stage<64, 24, 0, 8, 0, true>(d, A, sb, db, nw);
        mma_stage<64, 25, 8, 8, 1, false>(d, A, sb, db, nw);
        mma_stage<64, 26, 16, 7, 1, false>(d, A, sb, db, nw, [&](int k) {
            if (k == 1) {
                mbar_wait_cluster(sb + B_PO + warp * 8, 0);
#pragma unroll
                for (int s = 0; s < 7; ++s) lds4(&A[92 + 4 * s], sb + X_PL + warp * 3584 + s * 512 + lane * 16);
                if (lane == 0) mbar_arrive_remote(peer + B_DONE);
            }
        });
        wg_fence();
        mma_stage<64, 27, 23, 7, 2, false>(d, A, sb, db, nw);
        chunk_end<27>(sb);
        TS(g, 27);
        g2_store(0);
        TS(g, 28);
#define G2_CHUNK(C, NEXT) \
        chunk_begin<24 + 4 * C>(maps, db, sb, g); \
        mma_stage<64, 24 + 4 * C, 0, 8, 0, true>(d, A, sb, db, NEXT); \
        mma_stage<64, 25 + 4 * C, 8, 8, 1, false>(d, A, sb, db, NEXT); \
        mma_stage<64, 26 + 4 * C, 16, 7, 1, false>(d, A, sb, db, NEXT); \
        mma_stage<64, 27 + 4 * C, 23, 7, 2, false>(d, A, sb, db, NEXT); \
        chunk_end<27 + 4 * C>(sb); \
        TS(g, 27 + 3 * C); \
        g2_store(C); \
        TS(g, 28 + 3 * C);
        G2_CHUNK(1, nw)
        G2_CHUNK(2, nw)
        G2_CHUNK(3, nw & 2)
        if (lane == 0) asm volatile("cp.async.bulk.wait_group.read 0;" ::: "memory");
        TS(g, 38);
    }
}

typedef CUresult (*EncodeFn)(CUtensorMap*, CUtensorMapDataType, cuuint32_t, void*, const cuuint64_t*, const cuuint64_t*, const cuuint32_t*, const cuuint32_t*,
                             CUtensorMapInterleave, CUtensorMapSwizzle, CUtensorMapL2promotion, CUtensorMapFloatOOBfill);

void make_map(EncodeFn enc, CUtensorMap* m, const void* base, int rank, const cuuint64_t* dims, const cuuint64_t* strides, const cuuint32_t* box) {
    const cuuint32_t es[3] = {1, 1, 1};
    enc(m, CU_TENSOR_MAP_DATA_TYPE_BFLOAT16, rank, const_cast<void*>(base), dims, strides, box, es, CU_TENSOR_MAP_INTERLEAVE_NONE,
        CU_TENSOR_MAP_SWIZZLE_128B, CU_TENSOR_MAP_L2_PROMOTION_L2_128B, CU_TENSOR_MAP_FLOAT_OOB_FILL_NONE);
}
void make_map2(EncodeFn enc, CUtensorMap* m, const void* base, int cols, int rows, int box_rows) {
    const cuuint64_t dims[2] = {(cuuint64_t)cols, (cuuint64_t)rows};
    const cuuint64_t strides[1] = {(cuuint64_t)cols * 2};
    const cuuint32_t box[2] = {64, (cuuint32_t)box_rows};
    make_map(enc, m, base, 2, dims, strides, box);
}

}

extern "C" void kernel_launch(void* const* d_in, const int* in_sizes, int n_in, void* d_out, int out_size) {
    (void)in_sizes; (void)n_in; (void)out_size;
    static EncodeFn enc = nullptr;
    if (!enc) {
        void* p = nullptr;
        cudaDriverEntryPointQueryResult qr;
        cudaGetDriverEntryPoint("cuTensorMapEncodeTiled", &p, cudaEnableDefault, &qr);
        enc = (EncodeFn)p;
        cudaFuncSetAttribute(fused_kernel, cudaFuncAttributeMaxDynamicSharedMemorySize, SMEM_BYTES);
    }
    Maps maps;
    {
        const cuuint64_t dims[3] = {64, S_, D_ / 64};
        const cuuint64_t strides[2] = {D_ * 2, 128};
        const cuuint32_t box[3] = {64, 64, 2};
        make_map(enc, &maps.x, d_in[0], 3, dims, strides, box);
    }
    for (int c = 0; c < 10; ++c) maps.desc[c] = ((uint64_t)0x40000040u << 32) | (1u << 16) | (uint64_t)((4 * c) % NSTG * (STG_BYTES >> 4));
    make_map2(enc, &maps.wqkv, d_in[1], 3 * D_, D_, 128);
    make_map2(enc, &maps.w1, d_in[4], F_, D_, 128);
    make_map2(enc, &maps.w2, d_in[6], D_, F_, 128);
    make_map2(enc, &maps.w2b, d_in[6], D_, F_, 48);
    make_map2(enc, &maps.wo, d_in[2], D_, D_, 64);
    make_map2(enc, &maps.oinit, d_out, D_, S_, 64);
    make_map2(enc, &maps.ored, d_out, D_, S_, 16);
    fused_kernel<<<NCTA, 384, SMEM_BYTES, cudaStreamPerThread>>>(maps, (const __nv_bfloat16*)d_in[5]);
}
```

```cpp
#include <cuda_runtime.h>
#include <cuda.h>
#include <cuda_bf16.h>
#include <stdint.h>

namespace {

constexpr int S_ = 2048, D_ = 512, F_ = 1376;
constexpr int NCTA = 128;
constexpr int NSTG = 6;
constexpr int STG_BYTES = 16384;
constexpr uint32_t SM_RING = 0;
constexpr uint32_t SM_XA = NSTG * STG_BYTES;
constexpr uint32_t X_PK = SM_XA;
constexpr uint32_t X_KVB = SM_XA + 32768;
constexpr uint32_t X_OWN = SM_XA + 36864;
constexpr uint32_t X_PF = SM_XA + 69632;
constexpr uint32_t X_PL = SM_XA + 102400;
constexpr uint32_t SM_MISC = SM_XA + 131072;
constexpr uint32_t B_XFULL = SM_MISC + 0;
constexpr uint32_t B_FULL = SM_MISC + 64;
constexpr uint32_t B_EMPTY = SM_MISC + 112;
constexpr uint32_t B_PF = SM_MISC + 160;
constexpr uint32_t B_PO = SM_MISC + 224;
constexpr uint32_t B_KVST = SM_MISC + 288;
constexpr uint32_t B_KVRDY = SM_MISC + 296;
constexpr uint32_t B_DONE = SM_MISC + 304;
constexpr uint32_t B_OINIT = SM_MISC + 328;
constexpr uint32_t SM_KVOFF = SM_MISC + 312;
constexpr uint32_t SM_BIAS = SM_MISC + 512;
constexpr uint32_t SM_TOTAL = SM_BIAS + 1536;
constexpr int SMEM_BYTES = SM_TOTAL + 1024;
constexpr int KV_HEAD = 384;
constexpr int KV_FLOATS = 4 * KV_HEAD;
#define PFWAIT 0
constexpr int SPIN_LIMIT = 1 << 16;
constexpr float LOG2E = 1.4426950408889634f, LN2 = 0.6931471805599453f;
constexpr uint32_t ONES2 = 0x3f803f80u;

struct alignas(64) Maps { CUtensorMap x, wqkv, w1, w2, w2b, wo, oinit, ored; uint64_t desc[10]; const char* w[4]; };

__device__ unsigned g_count;
__device__ __align__(16) float g_kv[2][8][KV_FLOATS];
#define TS(role, i)
#define TSH(i)

__device__ __forceinline__ uint32_t smem_u32(const void* p) { return (uint32_t)__cvta_generic_to_shared(p); }
__device__ __forceinline__ void mbar_init(uint32_t bar, uint32_t cnt) { asm volatile("mbarrier.init.shared::cta.b64 [%0], %1;" ::"r"(bar), "r"(cnt) : "memory"); }
__device__ __forceinline__ void mbar_expect_tx(uint32_t bar, uint32_t bytes) { asm volatile("mbarrier.arrive.expect_tx.shared::cta.b64 _, [%0], %1;" ::"r"(bar), "r"(bytes) : "memory"); }
__device__ __forceinline__ void mbar_arrive(uint32_t bar) { asm volatile("mbarrier.arrive.shared::cta.b64 _, [%0];" ::"r"(bar) : "memory"); }
__device__ __forceinline__ uint32_t mapa(uint32_t addr, uint32_t cta) { uint32_t r; asm("mapa.shared::cluster.u32 %0, %1, %2;" : "=r"(r) : "r"(addr), "r"(cta)); return r; }
__device__ __forceinline__ void mbar_arrive_remote(uint32_t raddr) { asm volatile("mbarrier.arrive.shared::cluster.b64 _, [%0];" ::"r"(raddr) : "memory"); }
#define WAIT_LOOP(SEM) \
    "mov.u32 it, 0;\n" \
    "LOOP: mbarrier.try_wait.parity" SEM ".shared::cta.b64 p, [%0], %1;\n" \
    "@p bra DONE;\n" \
    "add.u32 it, it, 1;\n" \
    "setp.lt.u32 p, it, %2;\n" \
    "@p bra LOOP;\n" \
    "trap;\n" \
    "DONE: }"
__device__ __forceinline__ void mbar_wait(uint32_t bar, uint32_t parity) {
    asm volatile("{.reg .pred p; .reg .u32 it;\n" WAIT_LOOP("") ::"r"(bar), "r"(parity), "n"(SPIN_LIMIT) : "memory");
}
__device__ __forceinline__ void mbar_wait_cluster(uint32_t bar, uint32_t parity) {
    asm volatile("{.reg .pred p; .reg .u32 it;\n" WAIT_LOOP(".acquire.cluster") ::"r"(bar), "r"(parity), "n"(SPIN_LIMIT) : "memory");
}
__device__ __forceinline__ void mbar_test(uint32_t bar, uint32_t parity) {
    asm volatile("mbarrier.test_wait.parity.shared::cta.b64 pfull, [%0], %1;" ::"r"(bar), "r"(parity) : "memory");
}
__device__ __forceinline__ void mbar_check(uint32_t bar, uint32_t parity) {
    asm volatile("{.reg .pred p; .reg .u32 it;\n@pfull bra DONE;\n" WAIT_LOOP("") ::"r"(bar), "r"(parity), "n"(SPIN_LIMIT) : "memory");
}
__device__ __forceinline__ bool elect_one() {
    uint32_t p;
    asm volatile("{.reg .pred p; elect.sync _|p, 0xffffffff; selp.u32 %0, 1, 0, p;}" : "=r"(p));
    return p;
}
__device__ __forceinline__ void mbar_arrive_lane0(uint32_t bar) { asm volatile("@plane0 mbarrier.arrive.shared::cta.b64 _, [%0];" ::"r"(bar) : "memory"); }
__device__ __forceinline__ void tma2d(uint32_t dst, const CUtensorMap* m, int c0, int c1, uint32_t bar) {
    asm volatile("cp.async.bulk.tensor.2d.shared::cluster.global.mbarrier::complete_tx::bytes [%0], [%1, {%3,%4}], [%2];" ::"r"(dst), "l"(m), "r"(bar), "r"(c0), "r"(c1) : "memory");
}
__device__ __forceinline__ void tma3d(uint32_t dst, const CUtensorMap* m, int c0, int c1, int c2, uint32_t bar) {
    asm volatile("cp.async.bulk.tensor.3d.shared::cluster.global.mbarrier::complete_tx::bytes [%0], [%1, {%3,%4,%5}], [%2];" ::"r"(dst), "l"(m), "r"(bar), "r"(c0), "r"(c1), "r"(c2) : "memory");
}
__device__ __forceinline__ void tma_store2d(const CUtensorMap* m, int c0, int c1, uint32_t src) {
    asm volatile("cp.async.bulk.tensor.2d.global.shared::cta.bulk_group [%0, {%2,%3}], [%1];" ::"l"(m), "r"(src), "r"(c0), "r"(c1) : "memory");
}
__device__ __forceinline__ void tma_red2d(const CUtensorMap* m, int c0, int c1, uint32_t src) {
    asm volatile("cp.reduce.async.bulk.tensor.2d.global.shared::cta.add.bulk_group [%0, {%2,%3}], [%1];" ::"l"(m), "r"(src), "r"(c0), "r"(c1) : "memory");
}
__device__ __forceinline__ void bulk_s2c(uint32_t rdst, uint32_t src, uint32_t bytes, uint32_t rbar) {
    asm volatile("cp.async.bulk.shared::cluster.shared::cta.mbarrier::complete_tx::bytes [%0], [%1], %2, [%3];" ::"r"(rdst), "r"(src), "r"(bytes), "r"(rbar) : "memory");
}
__device__ __forceinline__ void l2_prefetch(const void* p, uint32_t bytes) { asm volatile("cp.async.bulk.prefetch.L2.global [%0], %1;" ::"l"(p), "r"(bytes) : "memory"); }
__device__ __forceinline__ void map_prefetch(const CUtensorMap* m) { asm volatile("prefetch.tensormap [%0];" ::"l"(m) : "memory"); }
__device__ __forceinline__ void fence_async_smem() { asm volatile("fence.proxy.async.shared::cta;" ::: "memory"); }
__device__ __forceinline__ void fence_async_all() { asm volatile("fence.proxy.async;" ::: "memory"); }
__device__ __forceinline__ void bar_sync(int id, int n) { asm volatile("bar.sync %0, %1;" ::"r"(id), "r"(n) : "memory"); }
__device__ __forceinline__ void bar_arrive(int id, int n) { asm volatile("bar.arrive %0, %1;" ::"r"(id), "r"(n) : "memory"); }
__device__ __forceinline__ void ldsm4(uint32_t& a, uint32_t& b, uint32_t& c, uint32_t& d, uint32_t addr) {
    asm volatile("ldmatrix.sync.aligned.m8n8.x4.shared.b16 {%0,%1,%2,%3}, [%4];" : "=r"(a), "=r"(b), "=r"(c), "=r"(d) : "r"(addr) : "memory");
}
__device__ __forceinline__ void stsm4(uint32_t addr, uint32_t a, uint32_t b, uint32_t c, uint32_t d) {
    asm volatile("stmatrix.sync.aligned.m8n8.x4.shared.b16 [%0], {%1,%2,%3,%4};" ::"r"(addr), "r"(a), "r"(b), "r"(c), "r"(d) : "memory");
}
__device__ __forceinline__ void lds4(uint32_t* a, uint32_t addr) {
    asm volatile("ld.shared.v4.u32 {%0,%1,%2,%3}, [%4];" : "=r"(a[0]), "=r"(a[1]), "=r"(a[2]), "=r"(a[3]) : "r"(addr) : "memory");
}
__device__ __forceinline__ void lds4f(float* a, uint32_t addr) {
    asm volatile("ld.shared.v4.f32 {%0,%1,%2,%3}, [%4];" : "=f"(a[0]), "=f"(a[1]), "=f"(a[2]), "=f"(a[3]) : "r"(addr) : "memory");
}
__device__ __forceinline__ void sts4(uint32_t addr, uint32_t a, uint32_t b, uint32_t c, uint32_t d) {
    asm volatile("st.shared.v4.u32 [%0], {%1,%2,%3,%4};" ::"r"(addr), "r"(a), "r"(b), "r"(c), "r"(d) : "memory");
}
__device__ __forceinline__ void red8_if(uint32_t a, uint32_t b, const char* p, const float* v) {
    asm volatile("{.reg .pred p; setp.eq.u32 p, %0, %1;\n"
                 "@p red.relaxed.gpu.global.add.v4.f32 [%2], {%3,%4,%5,%6};\n"
                 "@p red.relaxed.gpu.global.add.v4.f32 [%2+512], {%7,%8,%9,%10};}"
                 ::"r"(a), "r"(b), "l"(p), "f"(v[0]), "f"(v[1]), "f"(v[2]), "f"(v[3]), "f"(v[4]), "f"(v[5]), "f"(v[6]), "f"(v[7]) : "memory");
}
__device__ __forceinline__ void red4_if(uint32_t a, uint32_t b, const char* p, const float* v) {
    asm volatile("{.reg .pred p; setp.eq.u32 p, %0, %1;\n"
                 "@p red.relaxed.gpu.global.add.v4.f32 [%2+1024], {%3,%4,%5,%6};}"
                 ::"r"(a), "r"(b), "l"(p), "f"(v[0]), "f"(v[1]), "f"(v[2]), "f"(v[3]) : "memory");
}
__device__ __forceinline__ uint32_t pack2(float lo, float hi) {
    uint32_t r;
    asm("cvt.rn.bf16x2.f32 %0, %1, %2;" : "=r"(r) : "f"(hi), "f"(lo));
    return r;
}
__device__ __forceinline__ void mma16816(float (&c)[4], uint32_t a0, uint32_t a1, uint32_t a2, uint32_t a3, uint32_t b0, uint32_t b1) {
    asm("mma.sync.aligned.m16n8k16.row.col.f32.bf16.bf16.f32 {%0,%1,%2,%3}, {%4,%5,%6,%7}, {%8,%9}, {%0,%1,%2,%3};"
        : "+f"(c[0]), "+f"(c[1]), "+f"(c[2]), "+f"(c[3]) : "r"(a0), "r"(a1), "r"(a2), "r"(a3), "r"(b0), "r"(b1));
}
__device__ __forceinline__ float ex2f(float x) { float y; asm("ex2.approx.ftz.f32 %0, %1;" : "=f"(y) : "f"(x)); return y; }
__device__ __forceinline__ float rcpf(float x) { float y; asm("rcp.approx.ftz.f32 %0, %1;" : "=f"(y) : "f"(x)); return y; }
__device__ __forceinline__ void wg_fence() { asm volatile("wgmma.fence.sync.aligned;" ::: "memory"); }
__device__ __forceinline__ void wg_commit() { asm volatile("wgmma.commit_group.sync.aligned;" ::: "memory"); }
template <int N> __device__ __forceinline__ void wg_wait() { asm volatile("wgmma.wait_group.sync.aligned %0;" ::"n"(N) : "memory"); }
__device__ __forceinline__ uint32_t desc_lo(uint32_t addr) { return (addr & 0x3FFFFu) >> 4; }

template <int N, bool ACC, int STEP> __device__ __forceinline__ void wgmma_rs(float (&d)[32], const uint32_t* a, uint64_t& db) {
    if constexpr (N == 64 && ACC) {
        asm volatile("{.reg .pred p; setp.ne.b32 p, 1, 0;\n"
            "wgmma.mma_async.sync.aligned.m64n64k16.f32.bf16.bf16 {%0,%1,%2,%3,%4,%5,%6,%7,%8,%9,%10,%11,%12,%13,%14,%15,%16,%17,%18,%19,%20,%21,%22,%23,%24,%25,%26,%27,%28,%29,%30,%31}, {%33,%34,%35,%36}, %32, p, 1, 1, 1;\n"
            "add.s64 %32, %32, %37;}\n"
            : "+f"(d[0]), "+f"(d[1]), "+f"(d[2]), "+f"(d[3]), "+f"(d[4]), "+f"(d[5]), "+f"(d[6]), "+f"(d[7]), "+f"(d[8]), "+f"(d[9]), "+f"(d[10]), "+f"(d[11]),
              "+f"(d[12]), "+f"(d[13]), "+f"(d[14]), "+f"(d[15]), "+f"(d[16]), "+f"(d[17]), "+f"(d[18]), "+f"(d[19]), "+f"(d[20]), "+f"(d[21]), "+f"(d[22]), "+f"(d[23]),
              "+f"(d[24]), "+f"(d[25]), "+f"(d[26]), "+f"(d[27]), "+f"(d[28]), "+f"(d[29]), "+f"(d[30]), "+f"(d[31]), "+l"(db)
            : "r"(a[0]), "r"(a[1]), "r"(a[2]), "r"(a[3]), "n"(STEP));
    } else if constexpr (N == 64) {
        asm volatile("{.reg .pred p; setp.ne.b32 p, 0, 0;\n"
            "wgmma.mma_async.sync.aligned.m64n64k16.f32.bf16.bf16 {%0,%1,%2,%3,%4,%5,%6,%7,%8,%9,%10,%11,%12,%13,%14,%15,%16,%17,%18,%19,%20,%21,%22,%23,%24,%25,%26,%27,%28,%29,%30,%31}, {%33,%34,%35,%36}, %32, p, 1, 1, 1;\n"
            "add.s64 %32, %32, %37;}\n"
            : "=f"(d[0]), "=f"(d[1]), "=f"(d[2]), "=f"(d[3]), "=f"(d[4]), "=f"(d[5]), "=f"(d[6]), "=f"(d[7]), "=f"(d[8]), "=f"(d[9]), "=f"(d[10]), "=f"(d[11]),
              "=f"(d[12]), "=f"(d[13]), "=f"(d[14]), "=f"(d[15]), "=f"(d[16]), "=f"(d[17]), "=f"(d[18]), "=f"(d[19]), "=f"(d[20]), "=f"(d[21]), "=f"(d[22]), "=f"(d[23]),
              "=f"(d[24]), "=f"(d[25]), "=f"(d[26]), "=f"(d[27]), "=f"(d[28]), "=f"(d[29]), "=f"(d[30]), "=f"(d[31]), "+l"(db)
            : "r"(a[0]), "r"(a[1]), "r"(a[2]), "r"(a[3]), "n"(STEP));
    } else {
        static_assert(N == 48 && ACC, "unsupported shape");
        asm volatile("{.reg .pred p; setp.ne.b32 p, 1, 0;\n"
            "wgmma.mma_async.sync.aligned.m64n48k16.f32.bf16.bf16 {%0,%1,%2,%3,%4,%5,%6,%7,%8,%9,%10,%11,%12,%13,%14,%15,%16,%17,%18,%19,%20,%21,%22,%23}, {%25,%26,%27,%28}, %24, p, 1, 1, 1;\n"
            "add.s64 %24, %24, %29;}\n"
            : "+f"(d[0]), "+f"(d[1]), "+f"(d[2]), "+f"(d[3]), "+f"(d[4]), "+f"(d[5]), "+f"(d[6]), "+f"(d[7]), "+f"(d[8]), "+f"(d[9]), "+f"(d[10]), "+f"(d[11]),
              "+f"(d[12]), "+f"(d[13]), "+f"(d[14]), "+f"(d[15]), "+f"(d[16]), "+f"(d[17]), "+f"(d[18]), "+f"(d[19]), "+f"(d[20]), "+f"(d[21]), "+f"(d[22]), "+f"(d[23]), "+l"(db)
            : "r"(a[0]), "r"(a[1]), "r"(a[2]), "r"(a[3]), "n"(STEP));
    }
}
template <bool ACC> __device__ __forceinline__ void wgmma_ss72t(float (&d)[36], uint32_t alo, uint32_t blo) {
    if constexpr (ACC) {
        asm volatile("{.reg .pred p; .reg .b64 da, db; setp.ne.b32 p, 1, 0; mov.b64 da, {%36, 0x40000040}; mov.b64 db, {%37, 0x40000040};\n"
            "wgmma.mma_async.sync.aligned.m64n72k16.f32.bf16.bf16 {%0,%1,%2,%3,%4,%5,%6,%7,%8,%9,%10,%11,%12,%13,%14,%15,%16,%17,%18,%19,%20,%21,%22,%23,%24,%25,%26,%27,%28,%29,%30,%31,%32,%33,%34,%35}, da, db, p, 1, 1, 1, 1;}\n"
            : "+f"(d[0]), "+f"(d[1]), "+f"(d[2]), "+f"(d[3]), "+f"(d[4]), "+f"(d[5]), "+f"(d[6]), "+f"(d[7]), "+f"(d[8]), "+f"(d[9]), "+f"(d[10]), "+f"(d[11]),
              "+f"(d[12]), "+f"(d[13]), "+f"(d[14]), "+f"(d[15]), "+f"(d[16]), "+f"(d[17]), "+f"(d[18]), "+f"(d[19]), "+f"(d[20]), "+f"(d[21]), "+f"(d[22]), "+f"(d[23]),
              "+f"(d[24]), "+f"(d[25]), "+f"(d[26]), "+f"(d[27]), "+f"(d[28]), "+f"(d[29]), "+f"(d[30]), "+f"(d[31]), "+f"(d[32]), "+f"(d[33]), "+f"(d[34]), "+f"(d[35])
            : "r"(alo), "r"(blo));
    } else {
        asm volatile("{.reg .pred p; .reg .b64 da, db; setp.ne.b32 p, 0, 0; mov.b64 da, {%36, 0x40000040}; mov.b64 db, {%37, 0x40000040};\n"
            "wgmma.mma_async.sync.aligned.m64n72k16.f32.bf16.bf16 {%0,%1,%2,%3,%4,%5,%6,%7,%8,%9,%10,%11,%12,%13,%14,%15,%16,%17,%18,%19,%20,%21,%22,%23,%24,%25,%26,%27,%28,%29,%30,%31,%32,%33,%34,%35}, da, db, p, 1, 1, 1, 1;}\n"
            : "=f"(d[0]), "=f"(d[1]), "=f"(d[2]), "=f"(d[3]), "=f"(d[4]), "=f"(d[5]), "=f"(d[6]), "=f"(d[7]), "=f"(d[8]), "=f"(d[9]), "=f"(d[10]), "=f"(d[11]),
              "=f"(d[12]), "=f"(d[13]), "=f"(d[14]), "=f"(d[15]), "=f"(d[16]), "=f"(d[17]), "=f"(d[18]), "=f"(d[19]), "=f"(d[20]), "=f"(d[21]), "=f"(d[22]), "=f"(d[23]),
              "=f"(d[24]), "=f"(d[25]), "=f"(d[26]), "=f"(d[27]), "=f"(d[28]), "=f"(d[29]), "=f"(d[30]), "=f"(d[31]), "=f"(d[32]), "=f"(d[33]), "=f"(d[34]), "=f"(d[35])
            : "r"(alo), "r"(blo));
    }
}
__device__ __forceinline__ void wgmma_ss24(float (&d)[12], uint32_t alo, uint32_t blo) {
        asm volatile("{.reg .pred p; .reg .b64 da, db; setp.ne.b32 p, 0, 0; mov.b64 da, {%12, 0x40000040}; mov.b64 db, {%13, 0x40000040};\n"
            "wgmma.mma_async.sync.aligned.m64n24k16.f32.bf16.bf16 {%0,%1,%2,%3,%4,%5,%6,%7,%8,%9,%10,%11}, da, db, p, 1, 1, 0, 1;}\n"
            : "=f"(d[0]), "=f"(d[1]), "=f"(d[2]), "=f"(d[3]), "=f"(d[4]), "=f"(d[5]), "=f"(d[6]), "=f"(d[7]), "=f"(d[8]), "=f"(d[9]), "=f"(d[10]), "=f"(d[11])
            : "r"(alo), "r"(blo));
}

__host__ __device__ constexpr uint32_t full_bar(int g) { return B_FULL + (g % NSTG) * 8; }
__host__ __device__ constexpr uint32_t empty_bar(int g) { return B_EMPTY + ((g + NSTG) % NSTG) * 8; }
__host__ __device__ constexpr uint32_t full_par(int g) { return (g / NSTG) & 1; }

struct NoHook { __device__ __forceinline__ void operator()(int) const {} };

template <int N, int G, int K0, int NK, int POS, bool ZERO, class Hook = NoHook>
__device__ __forceinline__ void mma_stage(float (&d)[32], const uint32_t (&A)[128], uint32_t sb, uint64_t& db, int next_wg, Hook hook = Hook()) {
#pragma unroll
    for (int k = 0; k < NK; ++k) {
        constexpr int LAST = (((G + 1) % NSTG) - (G % NSTG)) * (STG_BYTES >> 4) - (NK - 1) * 128;
        if (ZERO && k == 0) wgmma_rs<64, false, 128>(d, &A[(K0 + k) * 4], db);
        else if (k == NK - 1) wgmma_rs<N, true, LAST>(d, &A[(K0 + k) * 4], db);
        else wgmma_rs<N, true, 128>(d, &A[(K0 + k) * 4], db);
        hook(k);
        if (k == NK - 3) {
            if (POS == 2 && next_wg) bar_arrive(next_wg, 256);
            if (POS != 0) {
                wg_commit();
                wg_wait<1>();
                mbar_arrive_lane0(sb + empty_bar(G - 1));
            }
        }
        if (k == NK - 2 && G < 39) mbar_test(sb + full_bar(G + 1), full_par(G + 1));
    }
    wg_commit();
    if (POS != 2) mbar_check(sb + full_bar(G + 1), full_par(G + 1));
}
template <int G> __device__ __forceinline__ void chunk_begin(const Maps& maps, uint64_t& db, uint32_t sb, int g) {
    db = maps.desc[G / 4] + desc_lo(sb + SM_RING);
    if (G == 0) mbar_wait(sb + full_bar(G), full_par(G));
    bar_sync(1 + g, 256);
    wg_fence();
}
template <int G> __device__ __forceinline__ void chunk_end(uint32_t sb) {
    wg_wait<0>();
    if (G < 39) {
        mbar_arrive_lane0(sb + empty_bar(G));
        mbar_check(sb + full_bar(G + 1), full_par(G + 1));
    }
}
template <int N, int C, bool ZERO>
__device__ __forceinline__ void g1_mma(float (&d)[32], const uint32_t (&A)[128], uint32_t sb, uint64_t& db, int next_wg) {
    mma_stage<N, 4 * C, 0, 8, 0, ZERO>(d, A, sb, db, next_wg);
    mma_stage<N, 4 * C + 1, 8, 8, 1, false>(d, A, sb, db, next_wg);
    mma_stage<N, 4 * C + 2, 16, 8, 1, false>(d, A, sb, db, next_wg);
    mma_stage<N, 4 * C + 3, 24, 8, 2, false>(d, A, sb, db, next_wg);
}

__device__ __forceinline__ uint32_t phi2(float a, float b) {
    uint32_t r = pack2(fmaxf(fmaf(a, LN2, 1.f), ex2f(-fabsf(a))), fmaxf(fmaf(b, LN2, 1.f), ex2f(-fabsf(b))));
    asm("add.rn.bf16x2 %0, %0, %1;" : "+r"(r) : "r"(0x35863586u));
    return r;
}
__device__ __forceinline__ float mish(float t) {
    const float e = ex2f(t);
    return fmaf(t, rcpf(fmaf(e, fmaf(e, -0.5f, -1.f), -1.f)), t);
}
__device__ __forceinline__ void phi_tile(const float (&d)[32], uint32_t tile) {
#pragma unroll
    for (int u = 0; u < 4; ++u)
        stsm4(tile ^ (u << 5), phi2(d[8 * u], d[8 * u + 1]), phi2(d[8 * u + 2], d[8 * u + 3]), phi2(d[8 * u + 4], d[8 * u + 5]), phi2(d[8 * u + 6], d[8 * u + 7]));
}
template <int NU> __device__ __forceinline__ void load_bias(float (&d)[32], uint32_t addr) {
#pragma unroll
    for (int i = 0; i < 2 * NU; ++i) lds4f(&d[4 * i], addr + i * 64);
}

__global__ void __cluster_dims__(2, 1, 1) __launch_bounds__(384, 1)
fused_kernel(const __grid_constant__ Maps maps, const __nv_bfloat16* __restrict__ b1) {
    extern __shared__ uint8_t smem_raw[];
    const uint32_t sbw = __shfl_sync(0xffffffffu, ((smem_u32(smem_raw) + 1023u) & ~1023u) + (threadIdx.x >> 5), 0);
    const uint32_t sb = sbw & ~1023u;
    const int warp = sbw & 1023u;
    const int lane = threadIdx.x & 31;
    const int rank = blockIdx.x & 1;
    int mi, pr;
    {
        const int c = blockIdx.x >> 1;
        int g, m;
        if (c < 4) { g = 15; m = c; }
        else if (c < 36) { g = (c - 4) & 7; m = (c - 4) >> 3; }
        else { m = ((c - 36) * 37) >> 8; g = 8 + (c - 36) - 7 * m; }
        mi = (g & ~1) | (m & 1);
        pr = (g & 1) * 2 + (m >> 1);
    }
    const int j = pr * 2 + rank;
    const int row0 = mi * 128;
    if (warp == 8) {
        if (elect_one()) {
            mbar_init(sb + B_XFULL, 1);
            mbar_expect_tx(sb + B_XFULL, 16384);
            fence_async_smem();
            tma3d(sb + SM_XA, &maps.x, 0, row0, 0, sb + B_XFULL);
#pragma unroll
            for (int i = 1; i < 8; ++i) mbar_init(sb + B_XFULL + i * 8, 1);
#pragma unroll
            for (int i = 0; i < NSTG; ++i) mbar_init(sb + B_FULL + i * 8, 1);
            fence_async_smem();
#pragma unroll
            for (int i = 1; i < 8; ++i) {
                const int b = (i & 1) * 4 + (i >> 1);
                mbar_expect_tx(sb + B_XFULL + b * 8, 16384);
                tma3d(sb + SM_XA + b * 16384, &maps.x, 0, row0 + (b >> 2) * 64, (b & 3) * 2, sb + B_XFULL + b * 8);
            }
        }
        __syncwarp();
        TSH(17);
    }
    const uint32_t swz = (lane & 15) * 128 + (((lane >> 4) ^ (lane & 7)) << 4);

    if (warp >= 8) {
        asm volatile("setmaxnreg.dec.sync.aligned.u32 40;");
        if (warp == 8) {
            bar_arrive(3, 384);
            asm volatile("barrier.cluster.arrive.relaxed.aligned;" ::: "memory");
            TSH(16);
            if (elect_one()) {
#pragma unroll
                for (int i = 0; i < NSTG; ++i) mbar_init(sb + B_EMPTY + i * 8, 8);
            }
            __syncwarp();
#pragma unroll
            for (int g = 0; g < 40; ++g) {
                const int s = g & 3, c = g >> 2;
                const uint32_t dst = sb + SM_RING + (g % NSTG) * STG_BYTES, bar = sb + full_bar(g);
                if (g >= NSTG) mbar_wait(sb + empty_bar(g), full_par(g) ^ 1);
                if (elect_one()) {
                    if (c < 6) {
                        mbar_expect_tx(bar, STG_BYTES);
                        if (c >= 3) tma2d(dst, &maps.w1, 176 * j + 64 * (c - 3), s * 128, bar);
                        else tma2d(dst, &maps.wqkv, 64 * j + (c == 2 ? 0 : 512 * (c + 1)), s * 128, bar);
                    } else {
                        const int col = 256 * rank + 64 * (c - 6), jj = j ^ (s & 1);
                        if (s < 2) {
                            mbar_expect_tx(bar, STG_BYTES);
                            tma2d(dst, &maps.w2, col, 176 * jj, bar);
                        } else {
                            mbar_expect_tx(bar, 112 * 128);
                            tma2d(dst, &maps.wo, col, 64 * jj, bar);
                            tma2d(dst + 8192, &maps.w2b, col, 176 * jj + 128, bar);
                        }
                    }
                }
            }
            __syncwarp();
            asm volatile("barrier.cluster.wait.aligned;" ::: "memory");
            mbar_wait_cluster(sb + B_DONE, 0);
        } else if (warp == 11) {
            bar_sync(3, 384);
            mbar_wait(sb + B_XFULL, 0);
            const unsigned epoch = *(volatile unsigned*)&g_count >> 7;
            if (elect_one()) {
                l2_prefetch(maps.w[0] + blockIdx.x * (3 * D_ * D_ * 2 / NCTA), 3 * D_ * D_ * 2 / NCTA);
                l2_prefetch(maps.w[1] + blockIdx.x * (F_ * D_ * 2 / NCTA), F_ * D_ * 2 / NCTA);
                l2_prefetch(maps.w[2] + blockIdx.x * (F_ * D_ * 2 / NCTA), F_ * D_ * 2 / NCTA);
                l2_prefetch(maps.w[3] + blockIdx.x * (D_ * D_ * 2 / NCTA), D_ * D_ * 2 / NCTA);
                map_prefetch(&maps.w1); map_prefetch(&maps.w2); map_prefetch(&maps.w2b); map_prefetch(&maps.wo); map_prefetch(&maps.ored);
            }
            __syncwarp();
#pragma unroll
            for (int f = 0; f < 3; ++f) {
                const int col = 64 * f + 2 * lane;
                float lo = 0.f, hi = 0.f;
                if (col < 176 && 176 * j + col < F_) {
                    const uint32_t v = *(const uint32_t*)(b1 + 176 * j + col);
                    lo = __uint_as_float(v << 16) * LOG2E;
                    hi = __uint_as_float(v & 0xffff0000u) * LOG2E;
                }
                sts4(sb + SM_BIAS + f * 512 + lane * 16, __float_as_uint(lo), __float_as_uint(hi), __float_as_uint(lo), __float_as_uint(hi));
            }
            if (lane == 0) asm volatile("st.shared.u32 [%0], %1;" ::"r"(sb + SM_KVOFF), "r"(((epoch & 1) * 8 + j) * (KV_FLOATS * 4)) : "memory");
            if (lane < 24) *(float4*)&g_kv[(epoch & 1) ^ 1][j][mi * 96 + lane * 4] = make_float4(0.f, 0.f, 0.f, 0.f);
            asm volatile("barrier.cluster.arrive.release.aligned; barrier.cluster.wait.aligned;" ::: "memory");
        } else {
            const int hw = warp - 9;
            if (lane == 0) {
                if (hw == 0) {
#pragma unroll
                    for (int i = 0; i < 8; ++i) { mbar_init(sb + B_PF + i * 8, 1); mbar_init(sb + B_PO + i * 8, 1); }
#pragma unroll
                    for (int i = 0; i < 8; ++i) { mbar_expect_tx(sb + B_PF + i * 8, 4096); mbar_expect_tx(sb + B_PO + i * 8, 3584); }
                } else {
                    mbar_init(sb + B_KVST, 8);
                    mbar_init(sb + B_KVRDY, 2);
                    mbar_init(sb + B_OINIT, 1);
                    mbar_init(sb + B_DONE, 8);
                }
                asm volatile("fence.mbarrier_init.release.cluster;" ::: "memory");
            }
            __syncwarp();
            bar_sync(3, 384);
            mbar_wait(sb + B_XFULL, 0);
            const unsigned epoch = *(volatile unsigned*)&g_count >> 7;
            if (hw == 0 && elect_one()) {
                mbar_wait(sb + B_XFULL + (j >> 1) * 8, 0);
                tma_store2d(&maps.oinit, 64 * j, row0, sb + SM_XA + j * 8192);
                mbar_wait(sb + B_XFULL + (4 + (j >> 1)) * 8, 0);
                tma_store2d(&maps.oinit, 64 * j, row0 + 64, sb + SM_XA + 65536 + j * 8192);
                asm volatile("cp.async.bulk.commit_group; cp.async.bulk.wait_group.read 0;" ::: "memory");
            }
            __syncwarp();
            TSH(hw * 8 + 0);
            asm volatile("barrier.cluster.arrive.relaxed.aligned; barrier.cluster.wait.aligned;" ::: "memory");
            if (elect_one()) {
                if (hw == 0) {
                    asm volatile("cp.async.bulk.wait_group 0;" ::: "memory");
                    fence_async_all();
                    mbar_wait(sb + B_KVST, 0);
                    TSH(1);
                    asm volatile("fence.acq_rel.gpu; red.relaxed.gpu.global.add.u32 [%0], 1;" ::"l"(&g_count) : "memory");
                    TSH(2);
                } else {
                    mbar_wait(sb + B_KVST, 0);
                }
                const unsigned target = (epoch + 1) << 7;
                for (int it = 0;; ++it) {
                    unsigned v;
                    asm volatile("ld.acquire.gpu.global.u32 %0, [%1];" : "=r"(v) : "l"(&g_count) : "memory");
                    if ((int)(v - target) >= 0) break;
                    if (it > SPIN_LIMIT) asm volatile("trap;");
                }
            }
            __syncwarp();
            TSH(hw * 8 + 3);
            const float* gk = &g_kv[epoch & 1][j][hw * 2 * KV_HEAD];
#pragma unroll
            for (int h = 0; h < 2; ++h) {
                const float4 t0 = __ldcg((const float4*)(gk + h * KV_HEAD + lane * 4));
                const float4 t1 = __ldcg((const float4*)(gk + h * KV_HEAD + 128 + lane * 4));
                const float z = __ldcg(gk + h * KV_HEAD + 256 + (lane & 7) * 16 + ((lane >> 3) & 1) * 2);
                const uint32_t base = sb + X_KVB + hw * 2048;
                stsm4(base + (swz ^ (h << 6)), pack2(t0.x, t0.y), pack2(t0.z, t0.w), pack2(t1.x, t1.y), pack2(t1.z, t1.w));
                const uint32_t zz = pack2(z, z);
                if (lane < 16) sts4(base + lane * 128 + (((h * 4 + 2) ^ (lane & 7)) << 4), zz, zz, zz, zz);
            }
            fence_async_smem();
            __syncwarp();
            if (lane == 0) mbar_arrive(sb + B_KVRDY);
            TSH(hw * 8 + 4);
            if (hw == 0) {
                fence_async_all();
                __syncwarp();
                if (lane == 0) mbar_arrive(sb + B_OINIT);
                TSH(5);
            }
        }
    } else {
        asm volatile("setmaxnreg.inc.sync.aligned.u32 232;");
        asm volatile(".reg .pred pfull, plane0; setp.eq.u32 plane0, %0, 0;" ::"r"(lane));
        const int g = warp >> 2, wl = warp & 3;
        uint32_t A[128];
        float d[32];
        bar_sync(3, 384);
        {
            float st[4][4];
#pragma unroll
            for (int i = 0; i < 4; ++i)
#pragma unroll
                for (int k = 0; k < 4; ++k) st[i][k] = 0.f;
            const uint32_t xb = sb + SM_XA + g * 65536 + wl * 2048;
#pragma unroll
            for (int e = 0; e < 4; ++e) {
                mbar_wait(sb + B_XFULL + (g * 4 + e) * 8, 0);
                TS(g, e);
#pragma unroll
                for (int t = 0; t < 8; ++t) {
                    const int s = e * 8 + t;
                    ldsm4(A[4 * s], A[4 * s + 1], A[4 * s + 2], A[4 * s + 3], xb + (s >> 2) * 8192 + (swz ^ ((s & 3) << 5)));
                }
#pragma unroll
                for (int t = 0; t < 8; ++t) {
                    const int s = e * 8 + t;
                    mma16816(st[(t & 1) * 2], A[4 * s], ONES2, A[4 * s + 2], ONES2, A[4 * s], A[4 * s + 2]);
                    mma16816(st[(t & 1) * 2 + 1], A[4 * s + 1], ONES2, A[4 * s + 3], ONES2, A[4 * s + 1], A[4 * s + 3]);
                }
            }
            const int r = lane >> 2;
            const int src = 4 * r + (r >> 1);
            const bool odd = r & 1;
            const float q0 = __shfl_sync(0xffffffffu, odd ? st[0][1] + st[2][1] : st[0][0] + st[2][0], src);
            const float s0 = __shfl_sync(0xffffffffu, odd ? st[0][3] + st[2][3] : st[0][2] + st[2][2], src);
            const float q1 = __shfl_sync(0xffffffffu, odd ? st[1][1] + st[3][1] : st[1][0] + st[3][0], src);
            const float s1 = __shfl_sync(0xffffffffu, odd ? st[1][3] + st[3][3] : st[1][2] + st[3][2], src);
            if (g == 1) bar_arrive(1, 256);
            asm volatile("barrier.cluster.arrive.relaxed.aligned;" ::: "memory");
            const float m0 = s0 * (1.f / D_), m1 = s1 * (1.f / D_);
            const uint32_t rr = pack2(LOG2E * rsqrtf(fmaxf(fmaf(q0, 1.f / D_, -m0 * m0), 0.f) + 1e-5f), LOG2E * rsqrtf(fmaxf(fmaf(q1, 1.f / D_, -m1 * m1), 0.f) + 1e-5f));
            const float c0 = -m0 * __uint_as_float(rr << 16), c1 = -m1 * __uint_as_float(rr & 0xffff0000u);
            const uint32_t r0 = __byte_perm(rr, 0, 0x1010), r1 = __byte_perm(rr, 0, 0x3232), cc0 = pack2(c0, c0), cc1 = pack2(c1, c1);
#pragma unroll
            for (int i = 0; i < 128; ++i) asm("fma.rn.bf16x2 %0, %0, %1, %2;" : "+r"(A[i]) : "r"((i & 1) ? r1 : r0), "r"((i & 1) ? cc1 : cc0));
        }
        TS(g, 4);
        uint64_t db;
        const uint32_t tile = sb + X_PK + g * 16384 + wl * 2048;
        const uint32_t bias = sb + SM_BIAS + (lane & 3) * 16;
        const uint32_t peer = mapa(sb, rank ^ 1);
        const int nw = 2 - g;
        chunk_begin<0>(maps, db, sb, g);
        TS(g, 8);
        g1_mma<64, 0, true>(d, A, sb, db, nw);
        chunk_end<3>(sb);
        TS(g, 9);
        asm volatile("barrier.cluster.wait.aligned;" ::: "memory");
        phi_tile(d, tile + (X_OWN - X_PK) + swz);
        TS(g, 10);
        chunk_begin<4>(maps, db, sb, g);
        g1_mma<64, 1, true>(d, A, sb, db, nw);
        chunk_end<7>(sb);
        TS(g, 12);
#pragma unroll
        for (int u = 0; u < 4; ++u)
            stsm4((tile + 8192 + swz) ^ (u << 5), pack2(d[8 * u], d[8 * u + 1]), pack2(d[8 * u + 2], d[8 * u + 3]), pack2(d[8 * u + 4], d[8 * u + 5]), pack2(d[8 * u + 6], d[8 * u + 7]));
        sts4(sb + X_KVB + wl * 512 + lane * 16, ONES2, ONES2, ONES2, ONES2);
        fence_async_smem();
        TS(g, 13);
        {
            float kv[36];
            const uint32_t pk_lo = desc_lo(sb + X_OWN + g * 16384);
            const uint32_t v_lo = desc_lo(sb + X_PK + g * 16384 + 8192) + ((1536 - g * 1024) << 16);
            uint32_t off;
            asm volatile("ld.shared.u32 %0, [%1];" : "=r"(off) : "r"(sb + SM_KVOFF) : "memory");
            off += wl * (KV_HEAD * 4) + lane * 16;
            chunk_begin<8>(maps, db, sb, g);
            wgmma_ss72t<false>(kv, pk_lo, v_lo);
#pragma unroll
            for (int k = 1; k < 4; ++k) wgmma_ss72t<true>(kv, pk_lo + k * 128, v_lo + k * (128 - (128 << 16)));
            mma_stage<64, 8, 0, 8, 0, true>(d, A, sb, db, nw);
            mma_stage<64, 9, 8, 8, 1, false>(d, A, sb, db, nw);
            mma_stage<64, 10, 16, 8, 1, false>(d, A, sb, db, nw, [&](int k) {
                const char* gk = (const char*)&g_kv[0][0][0] + off;
                if (k < 4) red8_if(wl, k, gk, &kv[8 * k]);
                if (k == 4) red4_if(off & 48, 0, gk, &kv[32]);
                if (k == 5) { __syncwarp(); mbar_arrive_lane0(sb + B_KVST); }
            });
            mma_stage<64, 11, 24, 8, 2, false>(d, A, sb, db, nw);
            chunk_end<11>(sb);
            TS(g, 15);
        }
        phi_tile(d, tile + swz);
        load_bias<4>(d, bias);
        TS(g, 16);
        const uint32_t own = sb + X_OWN + warp * 4096;
#pragma unroll
        for (int f = 0; f < 2; ++f) {
            if (f == 0) { chunk_begin<12>(maps, db, sb, g); g1_mma<64, 3, false>(d, A, sb, db, nw); chunk_end<15>(sb); }
            else { chunk_begin<16>(maps, db, sb, g); g1_mma<64, 4, false>(d, A, sb, db, nw); chunk_end<19>(sb); }
            TS(g, 18 + 3 * f);
#pragma unroll
            for (int u = 0; u < 4; ++u)
                sts4(own + f * 2048 + u * 512 + lane * 16, pack2(mish(d[8 * u]), mish(d[8 * u + 1])), pack2(mish(d[8 * u + 2]), mish(d[8 * u + 3])),
                     pack2(mish(d[8 * u + 4]), mish(d[8 * u + 5])), pack2(mish(d[8 * u + 6]), mish(d[8 * u + 7])));
            fence_async_smem();
            __syncwarp();
            if (elect_one()) bulk_s2c(peer + X_PF + warp * 4096 + f * 2048, own + f * 2048, 2048, peer + B_PF + warp * 8);
            if (f == 0) load_bias<4>(d, bias + 512);
            else load_bias<3>(d, bias + 1024);
            TS(g, 19 + 3 * f);
        }
        {
            float o[4][12];
            const uint32_t pq_lo = desc_lo(sb + X_PK + g * 16384) | (1u << 16);
            const uint32_t kv_lo = desc_lo(sb + X_KVB) | (1u << 16);
            chunk_begin<20>(maps, db, sb, g);
            mma_stage<48, 20, 0, 8, 0, false>(d, A, sb, db, nw);
            mma_stage<48, 21, 8, 8, 1, false>(d, A, sb, db, nw);
            mma_stage<48, 22, 16, 8, 1, false>(d, A, sb, db, nw);
            mma_stage<48, 23, 24, 8, 2, false>(d, A, sb, db, 0);
            mbar_wait(sb + B_KVRDY, 0);
#pragma unroll
            for (int h = 0; h < 4; ++h) {
                wgmma_ss24(o[h], pq_lo + h * 2, kv_lo + (h >> 1) * 128 + (h & 1) * 4);
                if (h == 1) bar_arrive(nw, 256);
            }
            wg_commit();
            chunk_end<23>(sb);
            TS(g, 24);
#pragma unroll
            for (int h = 0; h < 4; ++h) {
                const float i0 = rcpf(o[h][8] + 1e-6f), i1 = rcpf(o[h][10] + 1e-6f);
                uint32_t* a = &A[64 + 4 * h];
                a[0] = pack2(o[h][0] * i0, o[h][1] * i0);
                a[1] = pack2(o[h][2] * i1, o[h][3] * i1);
                a[2] = pack2(o[h][4] * i0, o[h][5] * i0);
                a[3] = pack2(o[h][6] * i1, o[h][7] * i1);
                sts4(tile + h * 512 + lane * 16, a[0], a[1], a[2], a[3]);
            }
            fence_async_smem();
            __syncwarp();
            if (elect_one()) bulk_s2c(peer + X_PL + warp * 3584, tile, 2048, peer + B_PO + warp * 8);
#pragma unroll
            for (int u = 0; u < 3; ++u) {
                uint32_t* a = &A[80 + 4 * u];
#pragma unroll
                for (int i = 0; i < 4; ++i) a[i] = pack2(mish(d[8 * u + 2 * i]), mish(d[8 * u + 2 * i + 1]));
                sts4(tile + 8192 + u * 512 + lane * 16, a[0], a[1], a[2], a[3]);
            }
            fence_async_smem();
            __syncwarp();
            if (elect_one()) bulk_s2c(peer + X_PL + warp * 3584 + 2048, tile + 8192, 1536, peer + B_PO + warp * 8);
#pragma unroll
            for (int s = 0; s < 8; ++s) lds4(&A[4 * s], own + s * 512 + lane * 16);
            mbar_wait_cluster(sb + B_PF + warp * 8, 0);
#pragma unroll
            for (int s = 0; s < 8; ++s) lds4(&A[32 + 4 * s], sb + X_PF + warp * 4096 + s * 512 + lane * 16);
        }
        TS(g, 25);
        auto g2_store = [&](int c) {
            const uint32_t stg = sb + X_PF + warp * 4096 + (c & 1) * 2048;
            if (c >= 2) {
                asm volatile("cp.async.bulk.wait_group.read 1;" ::: "memory");
                __syncwarp();
            }
#pragma unroll
            for (int u = 0; u < 4; ++u)
                stsm4((stg + swz) ^ (u << 5), pack2(d[8 * u] * LN2, d[8 * u + 1] * LN2), pack2(d[8 * u + 2] * LN2, d[8 * u + 3] * LN2),
                      pack2(d[8 * u + 4] * LN2, d[8 * u + 5] * LN2), pack2(d[8 * u + 6] * LN2, d[8 * u + 7] * LN2));
            fence_async_smem();
            __syncwarp();
            if (c == 0) mbar_wait(sb + B_OINIT, 0);
            if (elect_one()) {
                tma_red2d(&maps.ored, 256 * rank + 64 * c, row0 + warp * 16, stg);
                asm volatile("cp.async.bulk.commit_group;" ::: "memory");
            }
        };
        chunk_begin<24>(maps, db, sb, g);
        mma_stage<64, 24, 0, 8, 0, true>(d, A, sb, db, nw);
        mma_stage<64, 25, 8, 8, 1, false>(d, A, sb, db, nw);
        mma_stage<64, 26, 16, 7, 1, false>(d, A, sb, db, nw, [&](int k) {
            if (k == 1) {
                mbar_wait_cluster(sb + B_PO + warp * 8, 0);
#pragma unroll
                for (int s = 0; s < 7; ++s) lds4(&A[92 + 4 * s], sb + X_PL + warp * 3584 + s * 512 + lane * 16);
                if (lane == 0) mbar_arrive_remote(peer + B_DONE);
            }
        });
        wg_fence();
        mma_stage<64, 27, 23, 7, 2, false>(d, A, sb, db, nw);
        chunk_end<27>(sb);
        TS(g, 27);
        g2_store(0);
        TS(g, 28);
#define G2_CHUNK(C, NEXT) \
        chunk_begin<24 + 4 * C>(maps, db, sb, g); \
        mma_stage<64, 24 + 4 * C, 0, 8, 0, true>(d, A, sb, db, NEXT); \
        mma_stage<64, 25 + 4 * C, 8, 8, 1, false>(d, A, sb, db, NEXT); \
        mma_stage<64, 26 + 4 * C, 16, 7, 1, false>(d, A, sb, db, NEXT); \
        mma_stage<64, 27 + 4 * C, 23, 7, 2, false>(d, A, sb, db, NEXT); \
        chunk_end<27 + 4 * C>(sb); \
        TS(g, 27 + 3 * C); \
        g2_store(C); \
        TS(g, 28 + 3 * C);
        G2_CHUNK(1, nw)
        G2_CHUNK(2, nw)
        G2_CHUNK(3, nw & 2)
        asm volatile("cp.async.bulk.wait_group.read 0;" ::: "memory");
        TS(g, 38);
    }
}

typedef CUresult (*EncodeFn)(CUtensorMap*, CUtensorMapDataType, cuuint32_t, void*, const cuuint64_t*, const cuuint64_t*, const cuuint32_t*, const cuuint32_t*,
                             CUtensorMapInterleave, CUtensorMapSwizzle, CUtensorMapL2promotion, CUtensorMapFloatOOBfill);

void make_map(EncodeFn enc, CUtensorMap* m, const void* base, int rank, const cuuint64_t* dims, const cuuint64_t* strides, const cuuint32_t* box) {
    const cuuint32_t es[3] = {1, 1, 1};
    enc(m, CU_TENSOR_MAP_DATA_TYPE_BFLOAT16, rank, const_cast<void*>(base), dims, strides, box, es, CU_TENSOR_MAP_INTERLEAVE_NONE,
        CU_TENSOR_MAP_SWIZZLE_128B, CU_TENSOR_MAP_L2_PROMOTION_L2_128B, CU_TENSOR_MAP_FLOAT_OOB_FILL_NONE);
}
void make_map2(EncodeFn enc, CUtensorMap* m, const void* base, int cols, int rows, int box_rows) {
    const cuuint64_t dims[2] = {(cuuint64_t)cols, (cuuint64_t)rows};
    const cuuint64_t strides[1] = {(cuuint64_t)cols * 2};
    const cuuint32_t box[2] = {64, (cuuint32_t)box_rows};
    make_map(enc, m, base, 2, dims, strides, box);
}

}

extern "C" void kernel_launch(void* const* d_in, const int* in_sizes, int n_in, void* d_out, int out_size) {
    (void)in_sizes; (void)n_in; (void)out_size;
    static EncodeFn enc = nullptr;
    if (!enc) {
        void* p = nullptr;
        cudaDriverEntryPointQueryResult qr;
        cudaGetDriverEntryPoint("cuTensorMapEncodeTiled", &p, cudaEnableDefault, &qr);
        enc = (EncodeFn)p;
        cudaFuncSetAttribute(fused_kernel, cudaFuncAttributeMaxDynamicSharedMemorySize, SMEM_BYTES);
    }
    Maps maps;
    {
        const cuuint64_t dims[3] = {64, S_, D_ / 64};
        const cuuint64_t strides[2] = {D_ * 2, 128};
        const cuuint32_t box[3] = {64, 64, 2};
        make_map(enc, &maps.x, d_in[0], 3, dims, strides, box);
    }
    for (int c = 0; c < 10; ++c) maps.desc[c] = ((uint64_t)0x40000040u << 32) | (1u << 16) | (uint64_t)((4 * c) % NSTG * (STG_BYTES >> 4));
    maps.w[0] = (const char*)d_in[1]; maps.w[1] = (const char*)d_in[4]; maps.w[2] = (const char*)d_in[6]; maps.w[3] = (const char*)d_in[2];
    make_map2(enc, &maps.wqkv, d_in[1], 3 * D_, D_, 128);
    make_map2(enc, &maps.w1, d_in[4], F_, D_, 128);
    make_map2(enc, &maps.w2, d_in[6], D_, F_, 128);
    make_map2(enc, &maps.w2b, d_in[6], D_, F_, 48);
    make_map2(enc, &maps.wo, d_in[2], D_, D_, 64);
    make_map2(enc, &maps.oinit, d_out, D_, S_, 64);
    make_map2(enc, &maps.ored, d_out, D_, S_, 16);
    fused_kernel<<<NCTA, 384, SMEM_BYTES, cudaStreamPerThread>>>(maps, (const __nv_bfloat16*)d_in[5]);
}
```

```cpp
#include <cuda_runtime.h>
#include <cuda.h>
#include <cuda_bf16.h>
#include <stdint.h>

namespace {

constexpr int S_ = 2048, D_ = 512, F_ = 1376;
constexpr int NCTA = 128;
constexpr int NSTG = 6;
constexpr int STG_BYTES = 16384;
constexpr uint32_t SM_RING = 0;
constexpr uint32_t SM_XA = NSTG * STG_BYTES;
constexpr uint32_t X_PK = SM_XA;
constexpr uint32_t X_KVB = SM_XA + 32768;
constexpr uint32_t X_OWN = SM_XA + 36864;
constexpr uint32_t X_PF = SM_XA + 69632;
constexpr uint32_t X_PL = SM_XA + 102400;
constexpr uint32_t SM_MISC = SM_XA + 131072;
constexpr uint32_t B_XFULL = SM_MISC + 0;
constexpr uint32_t B_FULL = SM_MISC + 64;
constexpr uint32_t B_EMPTY = SM_MISC + 112;
constexpr uint32_t B_PF = SM_MISC + 160;
constexpr uint32_t B_PO = SM_MISC + 224;
constexpr uint32_t B_KVST = SM_MISC + 288;
constexpr uint32_t B_KVRDY = SM_MISC + 296;
constexpr uint32_t B_DONE = SM_MISC + 304;
constexpr uint32_t B_OINIT = SM_MISC + 328;
constexpr uint32_t SM_KVOFF = SM_MISC + 312;
constexpr uint32_t SM_BIAS = SM_MISC + 512;
constexpr uint32_t SM_TOTAL = SM_BIAS + 1536;
constexpr int SMEM_BYTES = SM_TOTAL + 1024;
constexpr int KV_HEAD = 384;
constexpr int KV_FLOATS = 4 * KV_HEAD;
#define XDEF 4
#define HW11 (B_FULL)
#define HW9 (B_FULL)
#define DRY 1
#define XORD 0
constexpr int SPIN_LIMIT = 1 << 16;
constexpr float LOG2E = 1.4426950408889634f, LN2 = 0.6931471805599453f;
constexpr uint32_t ONES2 = 0x3f803f80u;

struct alignas(64) Maps { CUtensorMap x, wqkv, w1, w2, w2b, wo, oinit, ored; uint64_t desc[10]; const char* w[4]; uint32_t ident; };

__device__ unsigned g_count;
__device__ __align__(16) float g_kv[2][8][KV_FLOATS];
#define TS(role, i)
#define TSH(i)

__device__ __forceinline__ uint32_t smem_u32(const void* p) { return (uint32_t)__cvta_generic_to_shared(p); }
__device__ __forceinline__ void mbar_init(uint32_t bar, uint32_t cnt) { asm volatile("mbarrier.init.shared::cta.b64 [%0], %1;" ::"r"(bar), "r"(cnt) : "memory"); }
__device__ __forceinline__ void mbar_expect_tx(uint32_t bar, uint32_t bytes) { asm volatile("mbarrier.arrive.expect_tx.shared::cta.b64 _, [%0], %1;" ::"r"(bar), "r"(bytes) : "memory"); }
__device__ __forceinline__ void mbar_arrive(uint32_t bar) { asm volatile("mbarrier.arrive.shared::cta.b64 _, [%0];" ::"r"(bar) : "memory"); }
__device__ __forceinline__ uint32_t mapa(uint32_t addr, uint32_t cta) { uint32_t r; asm("mapa.shared::cluster.u32 %0, %1, %2;" : "=r"(r) : "r"(addr), "r"(cta)); return r; }
__device__ __forceinline__ void mbar_arrive_remote(uint32_t raddr) { asm volatile("mbarrier.arrive.shared::cluster.b64 _, [%0];" ::"r"(raddr) : "memory"); }
#define WAIT_LOOP(SEM) \
    "mov.u32 it, 0;\n" \
    "LOOP: mbarrier.try_wait.parity" SEM ".shared::cta.b64 p, [%0], %1;\n" \
    "@p bra DONE;\n" \
    "add.u32 it, it, 1;\n" \
    "setp.lt.u32 p, it, %2;\n" \
    "@p bra LOOP;\n" \
    "trap;\n" \
    "DONE: }"
__device__ __forceinline__ void mbar_wait(uint32_t bar, uint32_t parity) {
    asm volatile("{.reg .pred p; .reg .u32 it;\n" WAIT_LOOP("") ::"r"(bar), "r"(parity), "n"(SPIN_LIMIT) : "memory");
}
__device__ __forceinline__ void mbar_wait_cluster(uint32_t bar, uint32_t parity) {
    asm volatile("{.reg .pred p; .reg .u32 it;\n" WAIT_LOOP(".acquire.cluster") ::"r"(bar), "r"(parity), "n"(SPIN_LIMIT) : "memory");
}
__device__ __forceinline__ void mbar_test(uint32_t bar, uint32_t parity) {
    asm volatile("mbarrier.test_wait.parity.shared::cta.b64 pfull, [%0], %1;" ::"r"(bar), "r"(parity) : "memory");
}
__device__ __forceinline__ void mbar_check(uint32_t bar, uint32_t parity) {
    asm volatile("{.reg .pred p; .reg .u32 it;\n@pfull bra DONE;\n" WAIT_LOOP("") ::"r"(bar), "r"(parity), "n"(SPIN_LIMIT) : "memory");
}
__device__ __forceinline__ bool elect_one() {
    uint32_t p;
    asm volatile("{.reg .pred p; elect.sync _|p, 0xffffffff; selp.u32 %0, 1, 0, p;}" : "=r"(p));
    return p;
}
__device__ __forceinline__ void mbar_arrive_lane0(uint32_t bar) { asm volatile("@plane0 mbarrier.arrive.shared::cta.b64 _, [%0];" ::"r"(bar) : "memory"); }
__device__ __forceinline__ void tma2d(uint32_t dst, const CUtensorMap* m, int c0, int c1, uint32_t bar) {
    asm volatile("cp.async.bulk.tensor.2d.shared::cluster.global.mbarrier::complete_tx::bytes [%0], [%1, {%3,%4}], [%2];" ::"r"(dst), "l"(m), "r"(bar), "r"(c0), "r"(c1) : "memory");
}
__device__ __forceinline__ void tma3d(uint32_t dst, const CUtensorMap* m, int c0, int c1, int c2, uint32_t bar) {
    asm volatile("cp.async.bulk.tensor.3d.shared::cluster.global.mbarrier::complete_tx::bytes [%0], [%1, {%3,%4,%5}], [%2];" ::"r"(dst), "l"(m), "r"(bar), "r"(c0), "r"(c1), "r"(c2) : "memory");
}
__device__ __forceinline__ void tma_store2d(const CUtensorMap* m, int c0, int c1, uint32_t src) {
    asm volatile("cp.async.bulk.tensor.2d.global.shared::cta.bulk_group [%0, {%2,%3}], [%1];" ::"l"(m), "r"(src), "r"(c0), "r"(c1) : "memory");
}
__device__ __forceinline__ void tma_red2d(const CUtensorMap* m, int c0, int c1, uint32_t src) {
    asm volatile("cp.reduce.async.bulk.tensor.2d.global.shared::cta.add.bulk_group [%0, {%2,%3}], [%1];" ::"l"(m), "r"(src), "r"(c0), "r"(c1) : "memory");
}
__device__ __forceinline__ void bulk_s2c(uint32_t rdst, uint32_t src, uint32_t bytes, uint32_t rbar) {
    asm volatile("cp.async.bulk.shared::cluster.shared::cta.mbarrier::complete_tx::bytes [%0], [%1], %2, [%3];" ::"r"(rdst), "r"(src), "r"(bytes), "r"(rbar) : "memory");
}
__device__ __forceinline__ void l2_prefetch(const void* p, uint32_t bytes) { asm volatile("cp.async.bulk.prefetch.L2.global [%0], %1;" ::"l"(p), "r"(bytes) : "memory"); }
__device__ __forceinline__ void map_prefetch(const CUtensorMap* m) { asm volatile("prefetch.tensormap [%0];" ::"l"(m) : "memory"); }
__device__ __forceinline__ void fence_async_smem() { asm volatile("fence.proxy.async.shared::cta;" ::: "memory"); }
__device__ __forceinline__ void fence_async_all() { asm volatile("fence.proxy.async;" ::: "memory"); }
__device__ __forceinline__ void bar_sync(int id, int n) { asm volatile("bar.sync %0, %1;" ::"r"(id), "r"(n) : "memory"); }
__device__ __forceinline__ void bar_arrive(int id, int n) { asm volatile("bar.arrive %0, %1;" ::"r"(id), "r"(n) : "memory"); }
__device__ __forceinline__ void ldsm4(uint32_t& a, uint32_t& b, uint32_t& c, uint32_t& d, uint32_t addr) {
    asm volatile("ldmatrix.sync.aligned.m8n8.x4.shared.b16 {%0,%1,%2,%3}, [%4];" : "=r"(a), "=r"(b), "=r"(c), "=r"(d) : "r"(addr) : "memory");
}
__device__ __forceinline__ void stsm4(uint32_t addr, uint32_t a, uint32_t b, uint32_t c, uint32_t d) {
    asm volatile("stmatrix.sync.aligned.m8n8.x4.shared.b16 [%0], {%1,%2,%3,%4};" ::"r"(addr), "r"(a), "r"(b), "r"(c), "r"(d) : "memory");
}
__device__ __forceinline__ void lds4(uint32_t* a, uint32_t addr) {
    asm volatile("ld.shared.v4.u32 {%0,%1,%2,%3}, [%4];" : "=r"(a[0]), "=r"(a[1]), "=r"(a[2]), "=r"(a[3]) : "r"(addr) : "memory");
}
__device__ __forceinline__ void lds4f(float* a, uint32_t addr) {
    asm volatile("ld.shared.v4.f32 {%0,%1,%2,%3}, [%4];" : "=f"(a[0]), "=f"(a[1]), "=f"(a[2]), "=f"(a[3]) : "r"(addr) : "memory");
}
__device__ __forceinline__ void sts4(uint32_t addr, uint32_t a, uint32_t b, uint32_t c, uint32_t d) {
    asm volatile("st.shared.v4.u32 [%0], {%1,%2,%3,%4};" ::"r"(addr), "r"(a), "r"(b), "r"(c), "r"(d) : "memory");
}
__device__ __forceinline__ void red8_if(uint32_t a, uint32_t b, const char* p, const float* v) {
    asm volatile("{.reg .pred p; setp.eq.u32 p, %0, %1;\n"
                 "@p red.relaxed.gpu.global.add.v4.f32 [%2], {%3,%4,%5,%6};\n"
                 "@p red.relaxed.gpu.global.add.v4.f32 [%2+512], {%7,%8,%9,%10};}"
                 ::"r"(a), "r"(b), "l"(p), "f"(v[0]), "f"(v[1]), "f"(v[2]), "f"(v[3]), "f"(v[4]), "f"(v[5]), "f"(v[6]), "f"(v[7]) : "memory");
}
__device__ __forceinline__ void red4_if(uint32_t a, uint32_t b, const char* p, const float* v) {
    asm volatile("{.reg .pred p; setp.eq.u32 p, %0, %1;\n"
                 "@p red.relaxed.gpu.global.add.v4.f32 [%2+1024], {%3,%4,%5,%6};}"
                 ::"r"(a), "r"(b), "l"(p), "f"(v[0]), "f"(v[1]), "f"(v[2]), "f"(v[3]) : "memory");
}
__device__ __forceinline__ uint32_t pack2(float lo, float hi) {
    uint32_t r;
    asm("cvt.rn.bf16x2.f32 %0, %1, %2;" : "=r"(r) : "f"(hi), "f"(lo));
    return r;
}
__device__ __forceinline__ void mma16816(float (&c)[4], uint32_t a0, uint32_t a1, uint32_t a2, uint32_t a3, uint32_t b0, uint32_t b1) {
    asm("mma.sync.aligned.m16n8k16.row.col.f32.bf16.bf16.f32 {%0,%1,%2,%3}, {%4,%5,%6,%7}, {%8,%9}, {%0,%1,%2,%3};"
        : "+f"(c[0]), "+f"(c[1]), "+f"(c[2]), "+f"(c[3]) : "r"(a0), "r"(a1), "r"(a2), "r"(a3), "r"(b0), "r"(b1));
}
__device__ __forceinline__ float ex2f(float x) { float y; asm("ex2.approx.ftz.f32 %0, %1;" : "=f"(y) : "f"(x)); return y; }
__device__ __forceinline__ float rsqf(float x) { float y; asm("rsqrt.approx.ftz.f32 %0, %1;" : "=f"(y) : "f"(x)); return y; }
__device__ __forceinline__ float rcpf(float x) { float y; asm("rcp.approx.ftz.f32 %0, %1;" : "=f"(y) : "f"(x)); return y; }
__device__ __forceinline__ void wg_fence() { asm volatile("wgmma.fence.sync.aligned;" ::: "memory"); }
__device__ __forceinline__ void wg_commit() { asm volatile("wgmma.commit_group.sync.aligned;" ::: "memory"); }
template <int N> __device__ __forceinline__ void wg_wait() { asm volatile("wgmma.wait_group.sync.aligned %0;" ::"n"(N) : "memory"); }
__device__ __forceinline__ uint32_t desc_lo(uint32_t addr) { return (addr & 0x3FFFFu) >> 4; }

template <int N, bool ACC, int STEP> __device__ __forceinline__ void wgmma_rs(float (&d)[32], const uint32_t* a, uint64_t& db) {
    if constexpr (N == 64 && ACC) {
        asm volatile("{.reg .pred p; setp.ne.b32 p, 1, 0;\n"
            "wgmma.mma_async.sync.aligned.m64n64k16.f32.bf16.bf16 {%0,%1,%2,%3,%4,%5,%6,%7,%8,%9,%10,%11,%12,%13,%14,%15,%16,%17,%18,%19,%20,%21,%22,%23,%24,%25,%26,%27,%28,%29,%30,%31}, {%33,%34,%35,%36}, %32, p, 1, 1, 1;\n"
            "add.s64 %32, %32, %37;}\n"
            : "+f"(d[0]), "+f"(d[1]), "+f"(d[2]), "+f"(d[3]), "+f"(d[4]), "+f"(d[5]), "+f"(d[6]), "+f"(d[7]), "+f"(d[8]), "+f"(d[9]), "+f"(d[10]), "+f"(d[11]),
              "+f"(d[12]), "+f"(d[13]), "+f"(d[14]), "+f"(d[15]), "+f"(d[16]), "+f"(d[17]), "+f"(d[18]), "+f"(d[19]), "+f"(d[20]), "+f"(d[21]), "+f"(d[22]), "+f"(d[23]),
              "+f"(d[24]), "+f"(d[25]), "+f"(d[26]), "+f"(d[27]), "+f"(d[28]), "+f"(d[29]), "+f"(d[30]), "+f"(d[31]), "+l"(db)
            : "r"(a[0]), "r"(a[1]), "r"(a[2]), "r"(a[3]), "n"(STEP));
    } else if constexpr (N == 64) {
        asm volatile("{.reg .pred p; setp.ne.b32 p, 0, 0;\n"
            "wgmma.mma_async.sync.aligned.m64n64k16.f32.bf16.bf16 {%0,%1,%2,%3,%4,%5,%6,%7,%8,%9,%10,%11,%12,%13,%14,%15,%16,%17,%18,%19,%20,%21,%22,%23,%24,%25,%26,%27,%28,%29,%30,%31}, {%33,%34,%35,%36}, %32, p, 1, 1, 1;\n"
            "add.s64 %32, %32, %37;}\n"
            : "=f"(d[0]), "=f"(d[1]), "=f"(d[2]), "=f"(d[3]), "=f"(d[4]), "=f"(d[5]), "=f"(d[6]), "=f"(d[7]), "=f"(d[8]), "=f"(d[9]), "=f"(d[10]), "=f"(d[11]),
              "=f"(d[12]), "=f"(d[13]), "=f"(d[14]), "=f"(d[15]), "=f"(d[16]), "=f"(d[17]), "=f"(d[18]), "=f"(d[19]), "=f"(d[20]), "=f"(d[21]), "=f"(d[22]), "=f"(d[23]),
              "=f"(d[24]), "=f"(d[25]), "=f"(d[26]), "=f"(d[27]), "=f"(d[28]), "=f"(d[29]), "=f"(d[30]), "=f"(d[31]), "+l"(db)
            : "r"(a[0]), "r"(a[1]), "r"(a[2]), "r"(a[3]), "n"(STEP));
    } else {
        static_assert(N == 48 && ACC, "unsupported shape");
        asm volatile("{.reg .pred p; setp.ne.b32 p, 1, 0;\n"
            "wgmma.mma_async.sync.aligned.m64n48k16.f32.bf16.bf16 {%0,%1,%2,%3,%4,%5,%6,%7,%8,%9,%10,%11,%12,%13,%14,%15,%16,%17,%18,%19,%20,%21,%22,%23}, {%25,%26,%27,%28}, %24, p, 1, 1, 1;\n"
            "add.s64 %24, %24, %29;}\n"
            : "+f"(d[0]), "+f"(d[1]), "+f"(d[2]), "+f"(d[3]), "+f"(d[4]), "+f"(d[5]), "+f"(d[6]), "+f"(d[7]), "+f"(d[8]), "+f"(d[9]), "+f"(d[10]), "+f"(d[11]),
              "+f"(d[12]), "+f"(d[13]), "+f"(d[14]), "+f"(d[15]), "+f"(d[16]), "+f"(d[17]), "+f"(d[18]), "+f"(d[19]), "+f"(d[20]), "+f"(d[21]), "+f"(d[22]), "+f"(d[23]), "+l"(db)
            : "r"(a[0]), "r"(a[1]), "r"(a[2]), "r"(a[3]), "n"(STEP));
    }
}
template <bool ACC> __device__ __forceinline__ void wgmma_ss72t(float (&d)[36], uint32_t alo, uint32_t blo) {
    if constexpr (ACC) {
        asm volatile("{.reg .pred p; .reg .b64 da, db; setp.ne.b32 p, 1, 0; mov.b64 da, {%36, 0x40000040}; mov.b64 db, {%37, 0x40000040};\n"
            "wgmma.mma_async.sync.aligned.m64n72k16.f32.bf16.bf16 {%0,%1,%2,%3,%4,%5,%6,%7,%8,%9,%10,%11,%12,%13,%14,%15,%16,%17,%18,%19,%20,%21,%22,%23,%24,%25,%26,%27,%28,%29,%30,%31,%32,%33,%34,%35}, da, db, p, 1, 1, 1, 1;}\n"
            : "+f"(d[0]), "+f"(d[1]), "+f"(d[2]), "+f"(d[3]), "+f"(d[4]), "+f"(d[5]), "+f"(d[6]), "+f"(d[7]), "+f"(d[8]), "+f"(d[9]), "+f"(d[10]), "+f"(d[11]),
              "+f"(d[12]), "+f"(d[13]), "+f"(d[14]), "+f"(d[15]), "+f"(d[16]), "+f"(d[17]), "+f"(d[18]), "+f"(d[19]), "+f"(d[20]), "+f"(d[21]), "+f"(d[22]), "+f"(d[23]),
              "+f"(d[24]), "+f"(d[25]), "+f"(d[26]), "+f"(d[27]), "+f"(d[28]), "+f"(d[29]), "+f"(d[30]), "+f"(d[31]), "+f"(d[32]), "+f"(d[33]), "+f"(d[34]), "+f"(d[35])
            : "r"(alo), "r"(blo));
    } else {
        asm volatile("{.reg .pred p; .reg .b64 da, db; setp.ne.b32 p, 0, 0; mov.b64 da, {%36, 0x40000040}; mov.b64 db, {%37, 0x40000040};\n"
            "wgmma.mma_async.sync.aligned.m64n72k16.f32.bf16.bf16 {%0,%1,%2,%3,%4,%5,%6,%7,%8,%9,%10,%11,%12,%13,%14,%15,%16,%17,%18,%19,%20,%21,%22,%23,%24,%25,%26,%27,%28,%29,%30,%31,%32,%33,%34,%35}, da, db, p, 1, 1, 1, 1;}\n"
            : "=f"(d[0]), "=f"(d[1]), "=f"(d[2]), "=f"(d[3]), "=f"(d[4]), "=f"(d[5]), "=f"(d[6]), "=f"(d[7]), "=f"(d[8]), "=f"(d[9]), "=f"(d[10]), "=f"(d[11]),
              "=f"(d[12]), "=f"(d[13]), "=f"(d[14]), "=f"(d[15]), "=f"(d[16]), "=f"(d[17]), "=f"(d[18]), "=f"(d[19]), "=f"(d[20]), "=f"(d[21]), "=f"(d[22]), "=f"(d[23]),
              "=f"(d[24]), "=f"(d[25]), "=f"(d[26]), "=f"(d[27]), "=f"(d[28]), "=f"(d[29]), "=f"(d[30]), "=f"(d[31]), "=f"(d[32]), "=f"(d[33]), "=f"(d[34]), "=f"(d[35])
            : "r"(alo), "r"(blo));
    }
}
__device__ __forceinline__ void wgmma_ss24(float (&d)[12], uint32_t alo, uint32_t blo) {
        asm volatile("{.reg .pred p; .reg .b64 da, db; setp.ne.b32 p, 0, 0; mov.b64 da, {%12, 0x40000040}; mov.b64 db, {%13, 0x40000040};\n"
            "wgmma.mma_async.sync.aligned.m64n24k16.f32.bf16.bf16 {%0,%1,%2,%3,%4,%5,%6,%7,%8,%9,%10,%11}, da, db, p, 1, 1, 0, 1;}\n"
            : "=f"(d[0]), "=f"(d[1]), "=f"(d[2]), "=f"(d[3]), "=f"(d[4]), "=f"(d[5]), "=f"(d[6]), "=f"(d[7]), "=f"(d[8]), "=f"(d[9]), "=f"(d[10]), "=f"(d[11])
            : "r"(alo), "r"(blo));
}

__host__ __device__ constexpr uint32_t full_bar(int g) { return B_FULL + (g % NSTG) * 8; }
__host__ __device__ constexpr uint32_t empty_bar(int g) { return B_EMPTY + ((g + NSTG) % NSTG) * 8; }
__host__ __device__ constexpr uint32_t full_par(int g) { return (g / NSTG) & 1; }

struct NoHook { __device__ __forceinline__ void operator()(int) const {} };

template <int N, int G, int K0, int NK, int POS, bool ZERO, class Hook = NoHook>
__device__ __forceinline__ void mma_stage(float (&d)[32], const uint32_t (&A)[128], uint32_t sb, uint64_t& db, int next_wg, Hook hook = Hook()) {
#pragma unroll
    for (int k = 0; k < NK; ++k) {
        constexpr int LAST = (((G + 1) % NSTG) - (G % NSTG)) * (STG_BYTES >> 4) - (NK - 1) * 128;
        if (ZERO && k == 0) wgmma_rs<64, false, 128>(d, &A[(K0 + k) * 4], db);
        else if (k == NK - 1) wgmma_rs<N, true, LAST>(d, &A[(K0 + k) * 4], db);
        else wgmma_rs<N, true, 128>(d, &A[(K0 + k) * 4], db);
        hook(k);
        if (k == NK - 3 && POS == 2 && next_wg) bar_arrive(next_wg, 256);
        if (k == NK - 3 && POS != 0) {
            wg_commit();
            wg_wait<1>();
            mbar_arrive_lane0(sb + empty_bar(G - 1));
        }
        if (k == NK - 2 && G < 39) mbar_test(sb + full_bar(G + 1), full_par(G + 1));
    }
    wg_commit();
    if (POS != 2) mbar_check(sb + full_bar(G + 1), full_par(G + 1));
}
template <int G> __device__ __forceinline__ void chunk_begin(const Maps& maps, uint64_t& db, uint32_t sb, int g) {
    db = maps.desc[G / 4] + desc_lo(sb + SM_RING);
    bar_sync(1 + g, 256);
    wg_fence();
}
template <int G> __device__ __forceinline__ void chunk_end(uint32_t sb) {
    wg_wait<0>();
    if (G < 39) {
        mbar_arrive_lane0(sb + empty_bar(G));
        mbar_check(sb + full_bar(G + 1), full_par(G + 1));
    }
}
template <int N, int C, bool ZERO>
__device__ __forceinline__ void g1_mma(float (&d)[32], const uint32_t (&A)[128], uint32_t sb, uint64_t& db, int next_wg) {
    mma_stage<N, 4 * C, 0, 8, 0, ZERO>(d, A, sb, db, next_wg);
    mma_stage<N, 4 * C + 1, 8, 8, 1, false>(d, A, sb, db, next_wg);
    mma_stage<N, 4 * C + 2, 16, 8, 1, false>(d, A, sb, db, next_wg);
    mma_stage<N, 4 * C + 3, 24, 8, 2, false>(d, A, sb, db, next_wg);
}

__device__ __forceinline__ uint32_t phi2(float a, float b) {
    uint32_t r = pack2(fmaxf(fmaf(a, LN2, 1.f), ex2f(-fabsf(a))), fmaxf(fmaf(b, LN2, 1.f), ex2f(-fabsf(b))));
    asm("add.rn.bf16x2 %0, %0, %1;" : "+r"(r) : "r"(0x35863586u));
    return r;
}
__device__ __forceinline__ float mish(float t) {
    const float e = ex2f(t);
    return fmaf(t, rcpf(fmaf(e, fmaf(e, -0.5f, -1.f), -1.f)), t);
}
__device__ __forceinline__ void phi_tile(const float (&d)[32], uint32_t tile) {
#pragma unroll
    for (int u = 0; u < 4; ++u)
        stsm4(tile ^ (u << 5), phi2(d[8 * u], d[8 * u + 1]), phi2(d[8 * u + 2], d[8 * u + 3]), phi2(d[8 * u + 4], d[8 * u + 5]), phi2(d[8 * u + 6], d[8 * u + 7]));
}
template <int NU> __device__ __forceinline__ void load_bias(float (&d)[32], uint32_t addr) {
#pragma unroll
    for (int i = 0; i < 2 * NU; ++i) lds4f(&d[4 * i], addr + i * 64);
}

__global__ void __cluster_dims__(2, 1, 1) __launch_bounds__(384, 1)
fused_kernel(const __grid_constant__ Maps maps, const __nv_bfloat16* __restrict__ b1) {
    extern __shared__ uint8_t smem_raw[];
    const uint32_t sbw = __shfl_sync(0xffffffffu, ((smem_u32(smem_raw) + 1023u) & ~1023u) + (threadIdx.x >> 5), 0);
    const uint32_t sb = sbw & ~1023u;
    const int warp = sbw & 1023u;
    const int lane = threadIdx.x & 31;
    const int rank = blockIdx.x & 1;
    int mi, pr;
    {
        const int c = blockIdx.x >> 1;
        int g, m;
        if (c < 4) { g = 15; m = c; }
        else if (c < 36) { g = (c - 4) & 7; m = (c - 4) >> 3; }
        else { m = ((c - 36) * 37) >> 8; g = 8 + (c - 36) - 7 * m; }
        mi = (g & ~1) | (m & 1);
        pr = (g & 1) * 2 + (m >> 1);
    }
    const int j = pr * 2 + rank;
    const int row0 = mi * 128;
    if (warp == 0) {
        if (elect_one()) {
            mbar_init(sb + B_XFULL, 1);
            mbar_expect_tx(sb + B_XFULL, 16384);
            fence_async_smem();
            tma3d(sb + SM_XA, &maps.x, 0, row0, 0, sb + B_XFULL);
#pragma unroll
            for (int i = 1; i < 8; ++i) mbar_init(sb + B_XFULL + i * 8, 1);
#pragma unroll
            for (int i = 0; i < NSTG; ++i) mbar_init(sb + B_FULL + i * 8, 1);
            fence_async_smem();
#pragma unroll
            for (int i = 1; i < 8; ++i) {
                const int b = XORD ? (i & 1) * 4 + (i >> 1) : i;
                mbar_expect_tx(sb + B_XFULL + b * 8, 16384);
                tma3d(sb + SM_XA + b * 16384, &maps.x, 0, row0 + (b >> 2) * 64, (b & 3) * 2, sb + B_XFULL + b * 8);
            }
        }
        __syncwarp();
        TSH(17);
        bar_arrive(3, 256);
        bar_arrive(4, 160);
    }
    const uint32_t swz = (lane & 15) * 128 + (((lane >> 4) ^ (lane & 7)) << 4);

    if (warp >= 8) {
        TSH(20 + warp - 8);
        asm volatile("setmaxnreg.dec.sync.aligned.u32 40;");
        TSH(24 + warp - 8);
        if (warp == 8) {
            asm volatile("barrier.cluster.arrive.relaxed.aligned;" ::: "memory");
            bar_sync(3, 256);
            TSH(16);
            if (elect_one()) {
#pragma unroll
                for (int i = 0; i < NSTG; ++i) mbar_init(sb + B_EMPTY + i * 8, 8);
            }
            __syncwarp();
#pragma unroll
            for (int g = 0; g < 40; ++g) {
                const int s = g & 3, c = g >> 2;
                const uint32_t dst = sb + SM_RING + (g % NSTG) * STG_BYTES, bar = sb + full_bar(g);
                if (g >= NSTG) mbar_wait(sb + empty_bar(g), full_par(g) ^ 1);
                if (elect_one()) {
                    if (c < 6) {
                        mbar_expect_tx(bar, STG_BYTES);
                        if (c >= 3) tma2d(dst, &maps.w1, 176 * j + 64 * (c - 3), s * 128, bar);
                        else tma2d(dst, &maps.wqkv, 64 * j + (c == 2 ? 0 : 512 * (c + 1)), s * 128, bar);
                    } else {
                        const int col = 256 * rank + 64 * (c - 6), jj = j ^ (s & 1);
                        if (s < 2) {
                            mbar_expect_tx(bar, STG_BYTES);
                            tma2d(dst, &maps.w2, col, 176 * jj, bar);
                        } else {
                            mbar_expect_tx(bar, 112 * 128);
                            tma2d(dst, &maps.wo, col, 64 * jj, bar);
                            tma2d(dst + 8192, &maps.w2b, col, 176 * jj + 128, bar);
                        }
                    }
                }
            }
            __syncwarp();
            asm volatile("barrier.cluster.wait.aligned;" ::: "memory");
            mbar_wait_cluster(sb + B_DONE, 0);
        } else if (warp == 11) {
            bar_sync(3, 256);
            mbar_wait(sb + HW11, 0);
            const unsigned epoch = *(volatile unsigned*)&g_count >> 7;
            if (elect_one()) {
                l2_prefetch(maps.w[0] + blockIdx.x * (3 * D_ * D_ * 2 / NCTA), 3 * D_ * D_ * 2 / NCTA);
                l2_prefetch(maps.w[1] + blockIdx.x * (F_ * D_ * 2 / NCTA), F_ * D_ * 2 / NCTA);
                l2_prefetch(maps.w[2] + blockIdx.x * (F_ * D_ * 2 / NCTA), F_ * D_ * 2 / NCTA);
                l2_prefetch(maps.w[3] + blockIdx.x * (D_ * D_ * 2 / NCTA), D_ * D_ * 2 / NCTA);
                map_prefetch(&maps.w1); map_prefetch(&maps.w2); map_prefetch(&maps.w2b); map_prefetch(&maps.wo); map_prefetch(&maps.ored);
            }
            __syncwarp();
#pragma unroll
            for (int f = 0; f < 3; ++f) {
                const int col = 64 * f + 2 * lane;
                float lo = 0.f, hi = 0.f;
                if (col < 176 && 176 * j + col < F_) {
                    const uint32_t v = *(const uint32_t*)(b1 + 176 * j + col);
                    lo = __uint_as_float(v << 16) * LOG2E;
                    hi = __uint_as_float(v & 0xffff0000u) * LOG2E;
                }
                sts4(sb + SM_BIAS + f * 512 + lane * 16, __float_as_uint(lo), __float_as_uint(hi), __float_as_uint(lo), __float_as_uint(hi));
            }
            if (lane == 0) asm volatile("st.shared.u32 [%0], %1;" ::"r"(sb + SM_KVOFF), "r"(((epoch & 1) * 8 + j) * (KV_FLOATS * 4)) : "memory");
            if (lane < 24) *(float4*)&g_kv[(epoch & 1) ^ 1][j][mi * 96 + lane * 4] = make_float4(0.f, 0.f, 0.f, 0.f);
            asm volatile("barrier.cluster.arrive.release.aligned; barrier.cluster.wait.aligned;" ::: "memory");
        } else {
            const int hw = warp - 9;
            if (lane == 0) {
                if (hw == 0) {
#pragma unroll
                    for (int i = 0; i < 8; ++i) { mbar_init(sb + B_PF + i * 8, 1); mbar_init(sb + B_PO + i * 8, 1); }
#pragma unroll
                    for (int i = 0; i < 8; ++i) { mbar_expect_tx(sb + B_PF + i * 8, 4096); mbar_expect_tx(sb + B_PO + i * 8, 3584); }
                } else {
                    mbar_init(sb + B_KVST, 8);
                    mbar_init(sb + B_KVRDY, 2);
                    mbar_init(sb + B_OINIT, 1);
                    mbar_init(sb + B_DONE, 8);
                }
                asm volatile("fence.mbarrier_init.release.cluster;" ::: "memory");
            }
            __syncwarp();
            bar_sync(3, 256);
            mbar_wait(sb + HW9, 0);
            const unsigned epoch = *(volatile unsigned*)&g_count >> 7;
            if (hw == 0 && elect_one()) {
                mbar_wait(sb + B_XFULL + (j >> 1) * 8, 0);
                tma_store2d(&maps.oinit, 64 * j, row0, sb + SM_XA + j * 8192);
                mbar_wait(sb + B_XFULL + (4 + (j >> 1)) * 8, 0);
                tma_store2d(&maps.oinit, 64 * j, row0 + 64, sb + SM_XA + 65536 + j * 8192);
                asm volatile("cp.async.bulk.commit_group; cp.async.bulk.wait_group.read 0;" ::: "memory");
            }
            __syncwarp();
            TSH(hw * 8 + 0);
            asm volatile("barrier.cluster.arrive.relaxed.aligned; barrier.cluster.wait.aligned;" ::: "memory");
            if (elect_one()) {
                if (hw == 0) {
                    asm volatile("cp.async.bulk.wait_group 0;" ::: "memory");
                    fence_async_all();
                    mbar_wait(sb + B_KVST, 0);
                    TSH(1);
                    asm volatile("fence.acq_rel.gpu; red.relaxed.gpu.global.add.u32 [%0], 1;" ::"l"(&g_count) : "memory");
                    TSH(2);
                } else {
                    mbar_wait(sb + B_KVST, 0);
                }
                const unsigned target = (epoch + 1) << 7;
                for (int it = 0;; ++it) {
                    unsigned v;
                    asm volatile("ld.acquire.gpu.global.u32 %0, [%1];" : "=r"(v) : "l"(&g_count) : "memory");
                    if ((int)(v - target) >= 0) break;
                    if (it > SPIN_LIMIT) asm volatile("trap;");
                }
            }
            __syncwarp();
            TSH(hw * 8 + 3);
            const float* gk = &g_kv[epoch & 1][j][hw * 2 * KV_HEAD];
#pragma unroll
            for (int h = 0; h < 2; ++h) {
                const float4 t0 = __ldcg((const float4*)(gk + h * KV_HEAD + lane * 4));
                const float4 t1 = __ldcg((const float4*)(gk + h * KV_HEAD + 128 + lane * 4));
                const float z = __ldcg(gk + h * KV_HEAD + 256 + (lane & 7) * 16 + ((lane >> 3) & 1) * 2);
                const uint32_t base = sb + X_KVB + hw * 2048;
                stsm4(base + (swz ^ (h << 6)), pack2(t0.x, t0.y), pack2(t0.z, t0.w), pack2(t1.x, t1.y), pack2(t1.z, t1.w));
                const uint32_t zz = pack2(z, z);
                if (lane < 16) sts4(base + lane * 128 + (((h * 4 + 2) ^ (lane & 7)) << 4), zz, zz, zz, zz);
            }
            fence_async_smem();
            __syncwarp();
            if (lane == 0) mbar_arrive(sb + B_KVRDY);
            TSH(hw * 8 + 4);
            if (hw == 0) {
                fence_async_all();
                __syncwarp();
                if (lane == 0) mbar_arrive(sb + B_OINIT);
                TSH(5);
            }
        }
    } else {
        TS(warp >> 2, 40);
        asm volatile("setmaxnreg.inc.sync.aligned.u32 232;");
        TS(warp >> 2, 41);
        asm volatile(".reg .pred pfull, plane0, preal; setp.eq.u32 plane0, %0, 0;" ::"r"(lane));
        const int g = warp >> 2, wl = warp & 3;
        uint32_t A[128];
        float d[32];
        uint64_t db;
        const uint32_t tile = sb + X_PK + g * 16384 + wl * 2048;
        const uint32_t bias = sb + SM_BIAS + (lane & 3) * 16;
        const uint32_t peer = mapa(sb, rank ^ 1);
        const int nw = 2 - g;
#pragma unroll 1
        for (int pass = DRY ? 1 - g : 1; pass < 2; ++pass) {
            asm volatile("setp.ne.u32 preal, %0, 0;" ::"r"(pass));
            if (pass && warp) bar_sync(3 + g, 256 - 96 * g);
            float st[4][4];
#pragma unroll
            for (int i = 0; i < 4; ++i)
#pragma unroll
                for (int k = 0; k < 4; ++k) st[i][k] = 0.f;
            const uint32_t xb = sb + SM_XA + g * 65536 + wl * 2048;
            const uint32_t lsw = ((lane & 7) + (lane >> 4) * 8) * 128 + ((((lane >> 3) & 1) ^ (lane & 7)) << 4);
            const uint32_t xf = sb + B_XFULL + g * 32;
#pragma unroll
            for (int e = 0; e < 4; ++e) {
                if (e == 0) asm volatile("{.reg .pred p; .reg .u32 it;\n@!preal bra DONE;\n" WAIT_LOOP("") ::"r"(xf), "r"(0), "n"(SPIN_LIMIT) : "memory");
                else asm volatile("{.reg .pred p; .reg .u32 it;\n@pfull bra DONE;\n@!preal bra DONE;\n" WAIT_LOOP("") ::"r"(xf + e * 8), "r"(0), "n"(SPIN_LIMIT) : "memory");
                if (e == 0 || e == 3) TS(g, e + (pass ? 0 : (e ? -2 : 7)));
#pragma unroll
                for (int t = 0; t < 8; ++t) {
                    const int s = e * 8 + t;
                    ldsm4(A[4 * s], A[4 * s + 1], A[4 * s + 2], A[4 * s + 3], xb + (s >> 2) * 8192 + (lsw ^ ((s & 3) << 5)));
                }
                if (e < 3) mbar_test(xf + e * 8 + 8, 0);
#pragma unroll
                for (int s = 0; s < 32; ++s)
                    if (s >= e * 8 - XDEF && (s < e * 8 + 8 - XDEF || e == 3)) {
                        mma16816(st[(s & 1) * 2], A[4 * s], ONES2, A[4 * s + 1], ONES2, A[4 * s], A[4 * s + 1]);
                        mma16816(st[(s & 1) * 2 + 1], A[4 * s + 2], ONES2, A[4 * s + 3], ONES2, A[4 * s + 2], A[4 * s + 3]);
                    }
            }
            asm volatile("@preal barrier.cluster.arrive.relaxed.aligned;" ::: "memory");
            TS(g, pass ? 5 : 2);
            if (g + pass == 2) {
                bar_sync(1, 256);
                mbar_wait(sb + B_XFULL, 0);
            }
            const int r = lane >> 2;
            const int src = 4 * r + (r >> 1);
            const bool odd = r & 1;
            const float q0 = __shfl_sync(0xffffffffu, odd ? st[0][1] + st[2][1] : st[0][0] + st[2][0], src);
            const float s0 = __shfl_sync(0xffffffffu, odd ? st[0][3] + st[2][3] : st[0][2] + st[2][2], src);
            const float q1 = __shfl_sync(0xffffffffu, odd ? st[1][1] + st[3][1] : st[1][0] + st[3][0], src);
            const float s1 = __shfl_sync(0xffffffffu, odd ? st[1][3] + st[3][3] : st[1][2] + st[3][2], src);
            const float m0 = s0 * (1.f / D_), m1 = s1 * (1.f / D_);
            const uint32_t rr = pack2(LOG2E * rsqf(fmaxf(fmaf(q0, 1.f / D_, -m0 * m0), 0.f) + 1e-5f), LOG2E * rsqf(fmaxf(fmaf(q1, 1.f / D_, -m1 * m1), 0.f) + 1e-5f));
            const float c0 = -m0 * __uint_as_float(rr << 16), c1 = -m1 * __uint_as_float(rr & 0xffff0000u);
            const uint32_t r0 = __byte_perm(rr, 0, 0x1010), r1 = __byte_perm(rr, 0, 0x3232), cc0 = pack2(c0, c0), cc1 = pack2(c1, c1);
#pragma unroll
            for (int s = 0; s < 32; ++s)
                asm volatile("{.reg .b32 t;\n"
                             "fma.rn.bf16x2 t, %1, %4, %5;\n"
                             "fma.rn.bf16x2 %0, %0, %4, %5;\n"
                             "fma.rn.bf16x2 %1, %2, %6, %7;\n"
                             "fma.rn.bf16x2 %3, %3, %6, %7;\n"
                             "prmt.b32 %2, t, t, %8;}"
                             : "+r"(A[4 * s]), "+r"(A[4 * s + 1]), "+r"(A[4 * s + 2]), "+r"(A[4 * s + 3]) : "r"(r0), "r"(cc0), "r"(r1), "r"(cc1), "r"(maps.ident));
            TS(g, 4);
        }
        mbar_wait(sb + full_bar(0), 0);
        TS(g, 6);
        chunk_begin<0>(maps, db, sb, g);
        TS(g, 8);
        g1_mma<64, 0, true>(d, A, sb, db, nw);
        chunk_end<3>(sb);
        TS(g, 9);
        const uint32_t pk = sb + SM_XA + g * 65536 + (j == 7 ? 6 : 7) * 8192;
        phi_tile(d, pk + wl * 2048 + swz);
        TS(g, 10);
        chunk_begin<4>(maps, db, sb, g);
        g1_mma<64, 1, true>(d, A, sb, db, nw);
        chunk_end<7>(sb);
        TS(g, 12);
        asm volatile("barrier.cluster.wait.aligned;" ::: "memory");
#pragma unroll
        for (int u = 0; u < 4; ++u)
            stsm4((tile + 8192 + swz) ^ (u << 5), pack2(d[8 * u], d[8 * u + 1]), pack2(d[8 * u + 2], d[8 * u + 3]), pack2(d[8 * u + 4], d[8 * u + 5]), pack2(d[8 * u + 6], d[8 * u + 7]));
        sts4(sb + X_KVB + wl * 512 + lane * 16, ONES2, ONES2, ONES2, ONES2);
        fence_async_smem();
        TS(g, 13);
        {
            float kv[36];
            const uint32_t pk_lo = desc_lo(pk);
            const uint32_t v_lo = desc_lo(sb + X_PK + g * 16384 + 8192) + ((1536 - g * 1024) << 16);
            uint32_t off;
            asm volatile("ld.shared.u32 %0, [%1];" : "=r"(off) : "r"(sb + SM_KVOFF) : "memory");
            off += wl * (KV_HEAD * 4) + lane * 16;
            chunk_begin<8>(maps, db, sb, g);
            wgmma_ss72t<false>(kv, pk_lo, v_lo);
#pragma unroll
            for (int k = 1; k < 4; ++k) wgmma_ss72t<true>(kv, pk_lo + k * 128, v_lo + k * (128 - (128 << 16)));
            mma_stage<64, 8, 0, 8, 0, true>(d, A, sb, db, nw);
            mma_stage<64, 9, 8, 8, 1, false>(d, A, sb, db, nw);
            mma_stage<64, 10, 16, 8, 1, false>(d, A, sb, db, nw, [&](int k) {
                const char* gk = (const char*)&g_kv[0][0][0] + off;
                if (k < 4) red8_if(wl, k, gk, &kv[8 * k]);
                if (k == 4) red4_if(off & 48, 0, gk, &kv[32]);
                if (k == 5) { __syncwarp(); mbar_arrive_lane0(sb + B_KVST); }
            });
            mma_stage<64, 11, 24, 8, 2, false>(d, A, sb, db, nw);
            chunk_end<11>(sb);
            TS(g, 15);
        }
        phi_tile(d, tile + swz);
        load_bias<4>(d, bias);
        TS(g, 16);
        const uint32_t own = sb + X_OWN + warp * 4096;
#pragma unroll
        for (int f = 0; f < 2; ++f) {
            if (f == 0) { chunk_begin<12>(maps, db, sb, g); g1_mma<64, 3, false>(d, A, sb, db, nw); chunk_end<15>(sb); }
            else { chunk_begin<16>(maps, db, sb, g); g1_mma<64, 4, false>(d, A, sb, db, nw); chunk_end<19>(sb); }
            TS(g, 18 + 3 * f);
#pragma unroll
            for (int u = 0; u < 4; ++u)
                sts4(own + f * 2048 + u * 512 + lane * 16, pack2(mish(d[8 * u]), mish(d[8 * u + 1])), pack2(mish(d[8 * u + 2]), mish(d[8 * u + 3])),
                     pack2(mish(d[8 * u + 4]), mish(d[8 * u + 5])), pack2(mish(d[8 * u + 6]), mish(d[8 * u + 7])));
            fence_async_smem();
            __syncwarp();
            if (elect_one()) bulk_s2c(peer + X_PF + warp * 4096 + f * 2048, own + f * 2048, 2048, peer + B_PF + warp * 8);
            if (f == 0) load_bias<4>(d, bias + 512);
            else load_bias<3>(d, bias + 1024);
            TS(g, 19 + 3 * f);
        }
        {
            float o[4][12];
            const uint32_t pq_lo = desc_lo(sb + X_PK + g * 16384) | (1u << 16);
            const uint32_t kv_lo = desc_lo(sb + X_KVB) | (1u << 16);
            chunk_begin<20>(maps, db, sb, g);
            mma_stage<48, 20, 0, 8, 0, false>(d, A, sb, db, nw);
            mma_stage<48, 21, 8, 8, 1, false>(d, A, sb, db, nw);
            mma_stage<48, 22, 16, 8, 1, false>(d, A, sb, db, nw);
            mma_stage<48, 23, 24, 8, 2, false>(d, A, sb, db, 0);
            mbar_wait(sb + B_KVRDY, 0);
#pragma unroll
            for (int h = 0; h < 4; ++h) {
                wgmma_ss24(o[h], pq_lo + h * 2, kv_lo + (h >> 1) * 128 + (h & 1) * 4);
                if (h == 1) bar_arrive(nw, 256);
            }
            wg_commit();
            chunk_end<23>(sb);
            TS(g, 24);
#pragma unroll
            for (int h = 0; h < 4; ++h) {
                const float i0 = rcpf(o[h][8] + 1e-6f), i1 = rcpf(o[h][10] + 1e-6f);
                uint32_t* a = &A[64 + 4 * h];
                a[0] = pack2(o[h][0] * i0, o[h][1] * i0);
                a[1] = pack2(o[h][2] * i1, o[h][3] * i1);
                a[2] = pack2(o[h][4] * i0, o[h][5] * i0);
                a[3] = pack2(o[h][6] * i1, o[h][7] * i1);
                sts4(tile + h * 512 + lane * 16, a[0], a[1], a[2], a[3]);
            }
            fence_async_smem();
            __syncwarp();
            if (elect_one()) bulk_s2c(peer + X_PL + warp * 3584, tile, 2048, peer + B_PO + warp * 8);
#pragma unroll
            for (int u = 0; u < 3; ++u) {
                uint32_t* a = &A[80 + 4 * u];
#pragma unroll
                for (int i = 0; i < 4; ++i) a[i] = pack2(mish(d[8 * u + 2 * i]), mish(d[8 * u + 2 * i + 1]));
                sts4(tile + 8192 + u * 512 + lane * 16, a[0], a[1], a[2], a[3]);
            }
            fence_async_smem();
            __syncwarp();
            if (elect_one()) bulk_s2c(peer + X_PL + warp * 3584 + 2048, tile + 8192, 1536, peer + B_PO + warp * 8);
#pragma unroll
            for (int s = 0; s < 8; ++s) lds4(&A[4 * s], own + s * 512 + lane * 16);
            mbar_wait_cluster(sb + B_PF + warp * 8, 0);
#pragma unroll
            for (int s = 0; s < 8; ++s) lds4(&A[32 + 4 * s], sb + X_PF + warp * 4096 + s * 512 + lane * 16);
        }
        TS(g, 25);
        auto g2_store = [&](int c) {
            const uint32_t stg = sb + X_PF + warp * 4096 + (c & 1) * 2048;
            if (c >= 2) {
                asm volatile("cp.async.bulk.wait_group.read 1;" ::: "memory");
                __syncwarp();
            }
#pragma unroll
            for (int u = 0; u < 4; ++u)
                stsm4((stg + swz) ^ (u << 5), pack2(d[8 * u] * LN2, d[8 * u + 1] * LN2), pack2(d[8 * u + 2] * LN2, d[8 * u + 3] * LN2),
                      pack2(d[8 * u + 4] * LN2, d[8 * u + 5] * LN2), pack2(d[8 * u + 6] * LN2, d[8 * u + 7] * LN2));
            fence_async_smem();
            __syncwarp();
            if (c == 0) mbar_wait(sb + B_OINIT, 0);
            if (elect_one()) {
                tma_red2d(&maps.ored, 256 * rank + 64 * c, row0 + warp * 16, stg);
                asm volatile("cp.async.bulk.commit_group;" ::: "memory");
            }
        };
        chunk_begin<24>(maps, db, sb, g);
        mma_stage<64, 24, 0, 8, 0, true>(d, A, sb, db, nw);
        mma_stage<64, 25, 8, 8, 1, false>(d, A, sb, db, nw);
        mma_stage<64, 26, 16, 7, 1, false>(d, A, sb, db, nw, [&](int k) {
            if (k == 1) {
                mbar_wait_cluster(sb + B_PO + warp * 8, 0);
#pragma unroll
                for (int s = 0; s < 7; ++s) lds4(&A[92 + 4 * s], sb + X_PL + warp * 3584 + s * 512 + lane * 16);
                if (lane == 0) mbar_arrive_remote(peer + B_DONE);
            }
        });
        wg_fence();
        mma_stage<64, 27, 23, 7, 2, false>(d, A, sb, db, nw);
        chunk_end<27>(sb);
        TS(g, 27);
        g2_store(0);
        TS(g, 28);
#define G2_CHUNK(C, NEXT) \
        chunk_begin<24 + 4 * C>(maps, db, sb, g); \
        mma_stage<64, 24 + 4 * C, 0, 8, 0, true>(d, A, sb, db, NEXT); \
        mma_stage<64, 25 + 4 * C, 8, 8, 1, false>(d, A, sb, db, NEXT); \
        mma_stage<64, 26 + 4 * C, 16, 7, 1, false>(d, A, sb, db, NEXT); \
        mma_stage<64, 27 + 4 * C, 23, 7, 2, false>(d, A, sb, db, NEXT); \
        chunk_end<27 + 4 * C>(sb); \
        TS(g, 27 + 3 * C); \
        g2_store(C); \
        TS(g, 28 + 3 * C);
        G2_CHUNK(1, nw)
        G2_CHUNK(2, nw)
        G2_CHUNK(3, nw & 2)
        asm volatile("cp.async.bulk.wait_group.read 0;" ::: "memory");
        TS(g, 38);
    }
}

typedef CUresult (*EncodeFn)(CUtensorMap*, CUtensorMapDataType, cuuint32_t, void*, const cuuint64_t*, const cuuint64_t*, const cuuint32_t*, const cuuint32_t*,
                             CUtensorMapInterleave, CUtensorMapSwizzle, CUtensorMapL2promotion, CUtensorMapFloatOOBfill);

void make_map(EncodeFn enc, CUtensorMap* m, const void* base, int rank, const cuuint64_t* dims, const cuuint64_t* strides, const cuuint32_t* box) {
    const cuuint32_t es[3] = {1, 1, 1};
    enc(m, CU_TENSOR_MAP_DATA_TYPE_BFLOAT16, rank, const_cast<void*>(base), dims, strides, box, es, CU_TENSOR_MAP_INTERLEAVE_NONE,
        CU_TENSOR_MAP_SWIZZLE_128B, CU_TENSOR_MAP_L2_PROMOTION_L2_128B, CU_TENSOR_MAP_FLOAT_OOB_FILL_NONE);
}
void make_map2(EncodeFn enc, CUtensorMap* m, const void* base, int cols, int rows, int box_rows) {
    const cuuint64_t dims[2] = {(cuuint64_t)cols, (cuuint64_t)rows};
    const cuuint64_t strides[1] = {(cuuint64_t)cols * 2};
    const cuuint32_t box[2] = {64, (cuuint32_t)box_rows};
    make_map(enc, m, base, 2, dims, strides, box);
}

}

extern "C" void kernel_launch(void* const* d_in, const int* in_sizes, int n_in, void* d_out, int out_size) {
    (void)in_sizes; (void)n_in; (void)out_size;
    static EncodeFn enc = nullptr;
    if (!enc) {
        void* p = nullptr;
        cudaDriverEntryPointQueryResult qr;
        cudaGetDriverEntryPoint("cuTensorMapEncodeTiled", &p, cudaEnableDefault, &qr);
        enc = (EncodeFn)p;
        cudaFuncSetAttribute(fused_kernel, cudaFuncAttributeMaxDynamicSharedMemorySize, SMEM_BYTES);
    }
    Maps maps;
    {
        const cuuint64_t dims[3] = {64, S_, D_ / 64};
        const cuuint64_t strides[2] = {D_ * 2, 128};
        const cuuint32_t box[3] = {64, 64, 2};
        make_map(enc, &maps.x, d_in[0], 3, dims, strides, box);
    }
    for (int c = 0; c < 10; ++c) maps.desc[c] = ((uint64_t)0x40000040u << 32) | (1u << 16) | (uint64_t)((4 * c) % NSTG * (STG_BYTES >> 4));
    maps.ident = 0x3210;
    maps.w[0] = (const char*)d_in[1]; maps.w[1] = (const char*)d_in[4]; maps.w[2] = (const char*)d_in[6]; maps.w[3] = (const char*)d_in[2];
    make_map2(enc, &maps.wqkv, d_in[1], 3 * D_, D_, 128);
    make_map2(enc, &maps.w1, d_in[4], F_, D_, 128);
    make_map2(enc, &maps.w2, d_in[6], D_, F_, 128);
    make_map2(enc, &maps.w2b, d_in[6], D_, F_, 48);
    make_map2(enc, &maps.wo, d_in[2], D_, D_, 64);
    make_map2(enc, &maps.oinit, d_out, D_, S_, 64);
    make_map2(enc, &maps.ored, d_out, D_, S_, 16);
    fused_kernel<<<NCTA, 384, SMEM_BYTES, cudaStreamPerThread>>>(maps, (const __nv_bfloat16*)d_in[5]);
}
```

```cpp
#include <cuda_runtime.h>
#include <cuda.h>
#include <cuda_bf16.h>
#include <stdint.h>

namespace {

constexpr int S_ = 2048, D_ = 512, F_ = 1376;
constexpr int NCTA = 128;
constexpr int NSTG = 6;
constexpr int NSLOT = 8;
constexpr int XSL = 10;
constexpr int STG_BYTES = 16384;
constexpr uint32_t SM_RING = 0;
constexpr uint32_t SM_XA = NSTG * STG_BYTES;
constexpr uint32_t X_PQ = SM_XA + 32768;
constexpr uint32_t X_KV = SM_XA + 40960;
constexpr uint32_t X_PF = SM_XA + 65536;
constexpr uint32_t X_KVB = SM_XA + 122880;
constexpr uint32_t X_OWN = SM_XA + 126976;
constexpr uint32_t SM_MISC = SM_XA + 131072;
constexpr uint32_t B_XFULL = SM_MISC + 0;
constexpr uint32_t B_FULL = SM_MISC + 64;
constexpr uint32_t B_EMPTY = SM_MISC + 128;
constexpr uint32_t B_PF = SM_MISC + 192;
constexpr uint32_t B_PO = SM_MISC + 256;
constexpr uint32_t B_KVST = SM_MISC + 320;
constexpr uint32_t B_KVRDY = SM_MISC + 328;
constexpr uint32_t B_DONE = SM_MISC + 336;
constexpr uint32_t B_OINIT = SM_MISC + 344;
constexpr uint32_t SM_KVOFF = SM_MISC + 352;
constexpr uint32_t SM_BIAS = SM_MISC + 512;
constexpr uint32_t SM_TOTAL = SM_BIAS + 768;
constexpr int SMEM_BYTES = SM_TOTAL + 1024;
constexpr int KV_HEAD = 384;
constexpr int KV_FLOATS = 4 * KV_HEAD;
constexpr int XDEF = 6;
constexpr int SPIN_LIMIT = 1 << 16;
constexpr float LOG2E = 1.4426950408889634f, LN2 = 0.6931471805599453f;
constexpr uint32_t ONES2 = 0x3f803f80u;

struct Args { const char* x; uint32_t ident; uint64_t desc[10]; const __nv_bfloat16* b1; const char* w[4]; char* out; };
struct alignas(64) Maps { CUtensorMap x, wqkv, w1, w2, w2b, wo, oinit, ored; };

__device__ unsigned g_count;
__device__ __align__(16) float g_kv[2][8][KV_FLOATS];

__device__ __forceinline__ uint32_t smem_u32(const void* p) { return (uint32_t)__cvta_generic_to_shared(p); }
__device__ __forceinline__ void mbar_init(uint32_t bar, uint32_t cnt) { asm volatile("mbarrier.init.shared::cta.b64 [%0], %1;" ::"r"(bar), "r"(cnt) : "memory"); }
__device__ __forceinline__ void mbar_expect_tx(uint32_t bar, uint32_t bytes) { asm volatile("mbarrier.arrive.expect_tx.shared::cta.b64 _, [%0], %1;" ::"r"(bar), "r"(bytes) : "memory"); }
__device__ __forceinline__ void mbar_arrive(uint32_t bar) { asm volatile("mbarrier.arrive.shared::cta.b64 _, [%0];" ::"r"(bar) : "memory"); }
__device__ __forceinline__ uint32_t mapa(uint32_t addr, uint32_t cta) { uint32_t r; asm("mapa.shared::cluster.u32 %0, %1, %2;" : "=r"(r) : "r"(addr), "r"(cta)); return r; }
#define WAIT_LOOP \
    "mov.u32 it, 0;\n" \
    "LOOP: mbarrier.try_wait.parity.shared::cta.b64 p, [%0], %1;\n" \
    "@p bra DONE;\n" \
    "add.u32 it, it, 1;\n" \
    "setp.lt.u32 p, it, %2;\n" \
    "@p bra LOOP;\n" \
    "trap;\n" \
    "DONE: }"
__device__ __forceinline__ void mbar_wait(uint32_t bar, uint32_t parity) {
    asm volatile("{.reg .pred p; .reg .u32 it;\n" WAIT_LOOP ::"r"(bar), "r"(parity), "n"(SPIN_LIMIT) : "memory");
}
__device__ __forceinline__ void mbar_test(uint32_t bar, uint32_t parity) {
    asm volatile("mbarrier.test_wait.parity.shared::cta.b64 pfull, [%0], %1;" ::"r"(bar), "r"(parity) : "memory");
}
__device__ __forceinline__ void mbar_check(uint32_t bar, uint32_t parity) {
    asm volatile("{.reg .pred p; .reg .u32 it;\n@pfull bra DONE;\n" WAIT_LOOP ::"r"(bar), "r"(parity), "n"(SPIN_LIMIT) : "memory");
}
__device__ __forceinline__ void aux_test(uint32_t bar) {
    asm volatile("mbarrier.test_wait.parity.shared::cta.b64 paux, [%0], 0;" ::"r"(bar) : "memory");
}
__device__ __forceinline__ void aux_check(uint32_t bar) {
    asm volatile("{.reg .pred p; .reg .u32 it;\n@paux bra DONE;\n" WAIT_LOOP ::"r"(bar), "r"(0), "n"(SPIN_LIMIT) : "memory");
}
__device__ __forceinline__ bool elect_one() {
    uint32_t p;
    asm volatile("{.reg .pred p; elect.sync _|p, 0xffffffff; selp.u32 %0, 1, 0, p;}" : "=r"(p));
    return p;
}
__device__ __forceinline__ void mbar_arrive_lane0(uint32_t bar) { asm volatile("@plane0 mbarrier.arrive.shared::cta.b64 _, [%0];" ::"r"(bar) : "memory"); }
__device__ __forceinline__ void tma2d(uint32_t dst, const CUtensorMap* m, int c0, int c1, uint32_t bar) {
    asm volatile("cp.async.bulk.tensor.2d.shared::cluster.global.mbarrier::complete_tx::bytes [%0], [%1, {%3,%4}], [%2];" ::"r"(dst), "l"(m), "r"(bar), "r"(c0), "r"(c1) : "memory");
}
__device__ __forceinline__ void tma3d(uint32_t dst, const CUtensorMap* m, int c0, int c1, int c2, uint32_t bar) {
    asm volatile("cp.async.bulk.tensor.3d.shared::cluster.global.mbarrier::complete_tx::bytes [%0], [%1, {%3,%4,%5}], [%2];" ::"r"(dst), "l"(m), "r"(bar), "r"(c0), "r"(c1), "r"(c2) : "memory");
}
__device__ __forceinline__ void tma_store2d(const CUtensorMap* m, int c0, int c1, uint32_t src) {
    asm volatile("cp.async.bulk.tensor.2d.global.shared::cta.bulk_group [%0, {%2,%3}], [%1];" ::"l"(m), "r"(src), "r"(c0), "r"(c1) : "memory");
}
__device__ __forceinline__ void tma_red2d(const CUtensorMap* m, int c0, int c1, uint32_t src) {
    asm volatile("cp.reduce.async.bulk.tensor.2d.global.shared::cta.add.bulk_group [%0, {%2,%3}], [%1];" ::"l"(m), "r"(src), "r"(c0), "r"(c1) : "memory");
}
__device__ __forceinline__ void st_async4(uint32_t raddr, const uint32_t* a, uint32_t rbar) {
    asm volatile("st.async.shared::cluster.mbarrier::complete_tx::bytes.v4.b32 [%0], {%1,%2,%3,%4}, [%5];" ::"r"(raddr), "r"(a[0]), "r"(a[1]), "r"(a[2]), "r"(a[3]), "r"(rbar) : "memory");
}
__device__ __forceinline__ void l2_prefetch(const void* p, uint32_t bytes) { asm volatile("cp.async.bulk.prefetch.L2.global [%0], %1;" ::"l"(p), "r"(bytes) : "memory"); }
__device__ __forceinline__ void map_prefetch(const CUtensorMap* m) { asm volatile("prefetch.tensormap [%0];" ::"l"(m) : "memory"); }
__device__ __forceinline__ void fence_async_smem() { asm volatile("fence.proxy.async.shared::cta;" ::: "memory"); }
__device__ __forceinline__ void fence_async_all() { asm volatile("fence.proxy.async;" ::: "memory"); }
__device__ __forceinline__ void bar_sync(int id, int n) { asm volatile("bar.sync %0, %1;" ::"r"(id), "r"(n) : "memory"); }
__device__ __forceinline__ void bar_arrive(int id, int n) { asm volatile("bar.arrive %0, %1;" ::"r"(id), "r"(n) : "memory"); }
__device__ __forceinline__ void ldsm4(uint32_t& a, uint32_t& b, uint32_t& c, uint32_t& d, uint32_t addr) {
    asm volatile("ldmatrix.sync.aligned.m8n8.x4.shared.b16 {%0,%1,%2,%3}, [%4];" : "=r"(a), "=r"(b), "=r"(c), "=r"(d) : "r"(addr) : "memory");
}
__device__ __forceinline__ void stsm4(uint32_t addr, uint32_t a, uint32_t b, uint32_t c, uint32_t d) {
    asm volatile("stmatrix.sync.aligned.m8n8.x4.shared.b16 [%0], {%1,%2,%3,%4};" ::"r"(addr), "r"(a), "r"(b), "r"(c), "r"(d) : "memory");
}
__device__ __forceinline__ void lds4(uint32_t* a, uint32_t addr) {
    asm volatile("ld.shared.v4.u32 {%0,%1,%2,%3}, [%4];" : "=r"(a[0]), "=r"(a[1]), "=r"(a[2]), "=r"(a[3]) : "r"(addr) : "memory");
}
__device__ __forceinline__ void sts4(uint32_t addr, uint32_t a, uint32_t b, uint32_t c, uint32_t d) {
    asm volatile("st.shared.v4.u32 [%0], {%1,%2,%3,%4};" ::"r"(addr), "r"(a), "r"(b), "r"(c), "r"(d) : "memory");
}
__device__ __forceinline__ void red8_if(uint32_t a, uint32_t b, const char* p, const float* v) {
    asm volatile("{.reg .pred p; setp.eq.u32 p, %0, %1;\n"
                 "@p red.relaxed.gpu.global.add.v4.f32 [%2], {%3,%4,%5,%6};\n"
                 "@p red.relaxed.gpu.global.add.v4.f32 [%2+512], {%7,%8,%9,%10};}"
                 ::"r"(a), "r"(b), "l"(p), "f"(v[0]), "f"(v[1]), "f"(v[2]), "f"(v[3]), "f"(v[4]), "f"(v[5]), "f"(v[6]), "f"(v[7]) : "memory");
}
__device__ __forceinline__ void red4_if(uint32_t a, uint32_t b, const char* p, const float* v) {
    asm volatile("{.reg .pred p; setp.eq.u32 p, %0, %1;\n"
                 "@p red.relaxed.gpu.global.add.v4.f32 [%2+1024], {%3,%4,%5,%6};}"
                 ::"r"(a), "r"(b), "l"(p), "f"(v[0]), "f"(v[1]), "f"(v[2]), "f"(v[3]) : "memory");
}
__device__ __forceinline__ uint32_t pack2(float lo, float hi) {
    uint32_t r;
    asm("cvt.rn.bf16x2.f32 %0, %1, %2;" : "=r"(r) : "f"(hi), "f"(lo));
    return r;
}
__device__ __forceinline__ void mma16816(float (&c)[4], uint32_t a0, uint32_t a1, uint32_t a2, uint32_t a3, uint32_t b0, uint32_t b1) {
    asm("mma.sync.aligned.m16n8k16.row.col.f32.bf16.bf16.f32 {%0,%1,%2,%3}, {%4,%5,%6,%7}, {%8,%9}, {%0,%1,%2,%3};"
        : "+f"(c[0]), "+f"(c[1]), "+f"(c[2]), "+f"(c[3]) : "r"(a0), "r"(a1), "r"(a2), "r"(a3), "r"(b0), "r"(b1));
}
__device__ __forceinline__ float ex2f(float x) { float y; asm("ex2.approx.ftz.f32 %0, %1;" : "=f"(y) : "f"(x)); return y; }
__device__ __forceinline__ float rsqf(float x) { float y; asm("rsqrt.approx.ftz.f32 %0, %1;" : "=f"(y) : "f"(x)); return y; }
__device__ __forceinline__ float rcpf(float x) { float y; asm("rcp.approx.ftz.f32 %0, %1;" : "=f"(y) : "f"(x)); return y; }
__device__ __forceinline__ void wg_fence() { asm volatile("wgmma.fence.sync.aligned;" ::: "memory"); }
__device__ __forceinline__ void wg_commit() { asm volatile("wgmma.commit_group.sync.aligned;" ::: "memory"); }
template <int N> __device__ __forceinline__ void wg_wait() { asm volatile("wgmma.wait_group.sync.aligned %0;" ::"n"(N) : "memory"); }
__device__ __forceinline__ uint32_t desc_lo(uint32_t addr) { return (addr & 0x3FFFFu) >> 4; }

template <int N, bool ACC, int STEP> __device__ __forceinline__ void wgmma_rs(float (&d)[32], const uint32_t* a, uint64_t& db) {
    if constexpr (N == 64 && ACC) {
        asm volatile("{.reg .pred p; setp.ne.b32 p, 1, 0;\n"
            "wgmma.mma_async.sync.aligned.m64n64k16.f32.bf16.bf16 {%0,%1,%2,%3,%4,%5,%6,%7,%8,%9,%10,%11,%12,%13,%14,%15,%16,%17,%18,%19,%20,%21,%22,%23,%24,%25,%26,%27,%28,%29,%30,%31}, {%33,%34,%35,%36}, %32, p, 1, 1, 1;\n"
            "add.s64 %32, %32, %37;}\n"
            : "+f"(d[0]), "+f"(d[1]), "+f"(d[2]), "+f"(d[3]), "+f"(d[4]), "+f"(d[5]), "+f"(d[6]), "+f"(d[7]), "+f"(d[8]), "+f"(d[9]), "+f"(d[10]), "+f"(d[11]),
              "+f"(d[12]), "+f"(d[13]), "+f"(d[14]), "+f"(d[15]), "+f"(d[16]), "+f"(d[17]), "+f"(d[18]), "+f"(d[19]), "+f"(d[20]), "+f"(d[21]), "+f"(d[22]), "+f"(d[23]),
              "+f"(d[24]), "+f"(d[25]), "+f"(d[26]), "+f"(d[27]), "+f"(d[28]), "+f"(d[29]), "+f"(d[30]), "+f"(d[31]), "+l"(db)
            : "r"(a[0]), "r"(a[1]), "r"(a[2]), "r"(a[3]), "n"(STEP));
    } else if constexpr (N == 64) {
        asm volatile("{.reg .pred p; setp.ne.b32 p, 0, 0;\n"
            "wgmma.mma_async.sync.aligned.m64n64k16.f32.bf16.bf16 {%0,%1,%2,%3,%4,%5,%6,%7,%8,%9,%10,%11,%12,%13,%14,%15,%16,%17,%18,%19,%20,%21,%22,%23,%24,%25,%26,%27,%28,%29,%30,%31}, {%33,%34,%35,%36}, %32, p, 1, 1, 1;\n"
            "add.s64 %32, %32, %37;}\n"
            : "=f"(d[0]), "=f"(d[1]), "=f"(d[2]), "=f"(d[3]), "=f"(d[4]), "=f"(d[5]), "=f"(d[6]), "=f"(d[7]), "=f"(d[8]), "=f"(d[9]), "=f"(d[10]), "=f"(d[11]),
              "=f"(d[12]), "=f"(d[13]), "=f"(d[14]), "=f"(d[15]), "=f"(d[16]), "=f"(d[17]), "=f"(d[18]), "=f"(d[19]), "=f"(d[20]), "=f"(d[21]), "=f"(d[22]), "=f"(d[23]),
              "=f"(d[24]), "=f"(d[25]), "=f"(d[26]), "=f"(d[27]), "=f"(d[28]), "=f"(d[29]), "=f"(d[30]), "=f"(d[31]), "+l"(db)
            : "r"(a[0]), "r"(a[1]), "r"(a[2]), "r"(a[3]), "n"(STEP));
    } else {
        static_assert(N == 48 && ACC, "unsupported shape");
        asm volatile("{.reg .pred p; setp.ne.b32 p, 1, 0;\n"
            "wgmma.mma_async.sync.aligned.m64n48k16.f32.bf16.bf16 {%0,%1,%2,%3,%4,%5,%6,%7,%8,%9,%10,%11,%12,%13,%14,%15,%16,%17,%18,%19,%20,%21,%22,%23}, {%25,%26,%27,%28}, %24, p, 1, 1, 1;\n"
            "add.s64 %24, %24, %29;}\n"
            : "+f"(d[0]), "+f"(d[1]), "+f"(d[2]), "+f"(d[3]), "+f"(d[4]), "+f"(d[5]), "+f"(d[6]), "+f"(d[7]), "+f"(d[8]), "+f"(d[9]), "+f"(d[10]), "+f"(d[11]),
              "+f"(d[12]), "+f"(d[13]), "+f"(d[14]), "+f"(d[15]), "+f"(d[16]), "+f"(d[17]), "+f"(d[18]), "+f"(d[19]), "+f"(d[20]), "+f"(d[21]), "+f"(d[22]), "+f"(d[23]), "+l"(db)
            : "r"(a[0]), "r"(a[1]), "r"(a[2]), "r"(a[3]), "n"(STEP));
    }
}
template <bool ACC> __device__ __forceinline__ void wgmma_ss72t(float (&d)[36], uint32_t alo, uint32_t blo) {
    if constexpr (ACC) {
        asm volatile("{.reg .pred p; .reg .b64 da, db; setp.ne.b32 p, 1, 0; mov.b64 da, {%36, 0x40000040}; mov.b64 db, {%37, 0x40000040};\n"
            "wgmma.mma_async.sync.aligned.m64n72k16.f32.bf16.bf16 {%0,%1,%2,%3,%4,%5,%6,%7,%8,%9,%10,%11,%12,%13,%14,%15,%16,%17,%18,%19,%20,%21,%22,%23,%24,%25,%26,%27,%28,%29,%30,%31,%32,%33,%34,%35}, da, db, p, 1, 1, 1, 1;}\n"
            : "+f"(d[0]), "+f"(d[1]), "+f"(d[2]), "+f"(d[3]), "+f"(d[4]), "+f"(d[5]), "+f"(d[6]), "+f"(d[7]), "+f"(d[8]), "+f"(d[9]), "+f"(d[10]), "+f"(d[11]),
              "+f"(d[12]), "+f"(d[13]), "+f"(d[14]), "+f"(d[15]), "+f"(d[16]), "+f"(d[17]), "+f"(d[18]), "+f"(d[19]), "+f"(d[20]), "+f"(d[21]), "+f"(d[22]), "+f"(d[23]),
              "+f"(d[24]), "+f"(d[25]), "+f"(d[26]), "+f"(d[27]), "+f"(d[28]), "+f"(d[29]), "+f"(d[30]), "+f"(d[31]), "+f"(d[32]), "+f"(d[33]), "+f"(d[34]), "+f"(d[35])
            : "r"(alo), "r"(blo));
    } else {
        asm volatile("{.reg .pred p; .reg .b64 da, db; setp.ne.b32 p, 0, 0; mov.b64 da, {%36, 0x40000040}; mov.b64 db, {%37, 0x40000040};\n"
            "wgmma.mma_async.sync.aligned.m64n72k16.f32.bf16.bf16 {%0,%1,%2,%3,%4,%5,%6,%7,%8,%9,%10,%11,%12,%13,%14,%15,%16,%17,%18,%19,%20,%21,%22,%23,%24,%25,%26,%27,%28,%29,%30,%31,%32,%33,%34,%35}, da, db, p, 1, 1, 1, 1;}\n"
            : "=f"(d[0]), "=f"(d[1]), "=f"(d[2]), "=f"(d[3]), "=f"(d[4]), "=f"(d[5]), "=f"(d[6]), "=f"(d[7]), "=f"(d[8]), "=f"(d[9]), "=f"(d[10]), "=f"(d[11]),
              "=f"(d[12]), "=f"(d[13]), "=f"(d[14]), "=f"(d[15]), "=f"(d[16]), "=f"(d[17]), "=f"(d[18]), "=f"(d[19]), "=f"(d[20]), "=f"(d[21]), "=f"(d[22]), "=f"(d[23]),
              "=f"(d[24]), "=f"(d[25]), "=f"(d[26]), "=f"(d[27]), "=f"(d[28]), "=f"(d[29]), "=f"(d[30]), "=f"(d[31]), "=f"(d[32]), "=f"(d[33]), "=f"(d[34]), "=f"(d[35])
            : "r"(alo), "r"(blo));
    }
}
__device__ __forceinline__ void wgmma_ss24(float (&d)[12], uint32_t alo, uint32_t blo) {
        asm volatile("{.reg .pred p; .reg .b64 da, db; setp.ne.b32 p, 0, 0; mov.b64 da, {%12, 0x40000040}; mov.b64 db, {%13, 0x40000040};\n"
            "wgmma.mma_async.sync.aligned.m64n24k16.f32.bf16.bf16 {%0,%1,%2,%3,%4,%5,%6,%7,%8,%9,%10,%11}, da, db, p, 1, 1, 0, 1;}\n"
            : "=f"(d[0]), "=f"(d[1]), "=f"(d[2]), "=f"(d[3]), "=f"(d[4]), "=f"(d[5]), "=f"(d[6]), "=f"(d[7]), "=f"(d[8]), "=f"(d[9]), "=f"(d[10]), "=f"(d[11])
            : "r"(alo), "r"(blo));
}

__host__ __device__ constexpr int slot_of(int g) {
    if (g < XSL) return g % 6;
    const int r = (g - XSL) % 8;
    return r < 2 ? 6 + r : (XSL + r - 2) % 6;
}
__host__ __device__ constexpr int use_of(int g) {
    if (g < XSL) return g / 6;
    return (g - XSL) / 8 + (slot_of(g) < 6 ? (XSL + 5 - slot_of(g)) / 6 : 0);
}
__host__ __device__ constexpr uint32_t full_bar(int g) { return B_FULL + slot_of(g) * 8; }
__host__ __device__ constexpr uint32_t empty_bar(int g) { return B_EMPTY + slot_of(g < 0 ? 0 : g) * 8; }
__host__ __device__ constexpr uint32_t full_par(int g) { return use_of(g) & 1; }

__host__ __device__ constexpr uint64_t slot_bits(int g0, int n) { uint64_t v = 0; for (int i = 0; i < n; ++i) v |= (uint64_t)slot_of(g0 + i) << (4 * i); return v; }
__host__ __device__ constexpr uint64_t par_bits() { uint64_t v = 0; for (int i = 0; i < 40; ++i) v |= (uint64_t)full_par(i) << i; return v; }
__host__ __device__ constexpr uint64_t reuse_bits() { uint64_t v = 0; for (int i = 0; i < 40; ++i) v |= (uint64_t)(use_of(i) > 0) << i; return v; }
constexpr uint64_t SLOTS0 = slot_bits(0, XSL), SLOTS1 = slot_bits(XSL, 8), PARS = par_bits(), REUSE = reuse_bits();
constexpr int LAST_REL = 39 - NSLOT;
template <int G> __device__ __forceinline__ void ring_test(uint32_t sb) { mbar_test(sb + full_bar(G), full_par(G)); }
template <int G> __device__ __forceinline__ void ring_check(uint32_t sb) { mbar_check(sb + full_bar(G), full_par(G)); }
struct NoHook { __device__ __forceinline__ void operator()(int) const {} };

template <int N, int G, int K0, int NK, int POS, bool ZERO, class Hook = NoHook>
__device__ __forceinline__ void mma_stage(float (&d)[32], const uint32_t (&A)[128], uint32_t sb, uint64_t& db, int next_wg, Hook hook = Hook()) {
    hook(-1);
#pragma unroll
    for (int k = 0; k < NK; ++k) {
        constexpr int LAST = (slot_of(G + 1) - slot_of(G)) * (STG_BYTES >> 4) - (NK - 1) * 128;
        if (ZERO && k == 0) wgmma_rs<64, false, 128>(d, &A[(K0 + k) * 4], db);
        else if (k == NK - 1) wgmma_rs<N, true, LAST>(d, &A[(K0 + k) * 4], db);
        else wgmma_rs<N, true, 128>(d, &A[(K0 + k) * 4], db);
        hook(k);
        if (k == NK - 3 && POS == 2 && next_wg) bar_arrive(next_wg, 256);
        if (k == NK - 3 && POS != 0 && G - 1 <= LAST_REL) {
            wg_commit();
            wg_wait<1>();
            mbar_arrive_lane0(sb + empty_bar(G - 1));
        }
        if (k == NK - 2 && G < 39) ring_test<G + 1>(sb);
    }
    if (POS == 2 || G <= LAST_REL) wg_commit();
    if (POS != 2) ring_check<G + 1>(sb);
}
template <int G> __device__ __forceinline__ void chunk_begin(const Args& args, uint64_t& db, uint32_t sb, int g) {
    db = args.desc[G / 4] + desc_lo(sb + SM_RING);
    if (G > 0) ring_check<G>(sb);
    bar_sync(1 + g, 256);
    wg_fence();
}
template <int G> __device__ __forceinline__ void chunk_end(uint32_t sb) {
    wg_wait<0>();
    if (G <= LAST_REL) mbar_arrive_lane0(sb + empty_bar(G));
}
template <int N, int C, bool ZERO>
__device__ __forceinline__ void g1_mma(float (&d)[32], const uint32_t (&A)[128], uint32_t sb, uint64_t& db, int next_wg) {
    mma_stage<N, 4 * C, 0, 8, 0, ZERO>(d, A, sb, db, next_wg);
    mma_stage<N, 4 * C + 1, 8, 8, 1, false>(d, A, sb, db, next_wg);
    mma_stage<N, 4 * C + 2, 16, 8, 1, false>(d, A, sb, db, next_wg);
    mma_stage<N, 4 * C + 3, 24, 8, 2, false>(d, A, sb, db, next_wg);
}

__device__ __forceinline__ uint32_t phi2(float a, float b) {
    uint32_t r = pack2(fmaxf(fmaf(a, LN2, 1.f), ex2f(-fabsf(a))), fmaxf(fmaf(b, LN2, 1.f), ex2f(-fabsf(b))));
    asm("add.rn.bf16x2 %0, %0, %1;" : "+r"(r) : "r"(0x35863586u));
    return r;
}
__device__ __forceinline__ float mish1(float t) {
    const float w = fmaf(ex2f(t), 0.70710678118654752f, 0.70710678118654752f);
    return fmaf(-t, rcpf(fmaf(w, w, 0.5f)), t);
}
__device__ __forceinline__ void mish4(const float* t, uint32_t* out) {
    out[0] = pack2(mish1(t[0]), mish1(t[1]));
    out[1] = pack2(mish1(t[2]), mish1(t[3]));
}
__device__ __forceinline__ void phi_tile(const float (&d)[32], uint32_t tile) {
#pragma unroll
    for (int u = 0; u < 4; ++u)
        stsm4(tile ^ (u << 5), phi2(d[8 * u], d[8 * u + 1]), phi2(d[8 * u + 2], d[8 * u + 3]), phi2(d[8 * u + 4], d[8 * u + 5]), phi2(d[8 * u + 6], d[8 * u + 7]));
}
__device__ __forceinline__ void load_bias16(float* d, uint32_t addr, uint32_t ident) {
    asm volatile("{.reg .b32 a, b;\n"
                 "ld.shared.v4.b32 {%0,%1,a,b}, [%8];\n"
                 "prmt.b32 %4, a, a, %9; prmt.b32 %5, b, b, %9; prmt.b32 %6, a, a, %9; prmt.b32 %7, b, b, %9; prmt.b32 %2, %0, %0, %9; prmt.b32 %3, %1, %1, %9;}"
                 : "=&f"(d[0]), "=&f"(d[1]), "=&f"(d[2]), "=&f"(d[3]), "=&f"(d[4]), "=&f"(d[5]), "=&f"(d[6]), "=&f"(d[7]) : "r"(addr), "r"(ident) : "memory");
}

__global__ void __cluster_dims__(2, 1, 1) __launch_bounds__(384, 1)
fused_kernel(const __grid_constant__ Args args, const __grid_constant__ Maps maps) {
    extern __shared__ uint8_t smem_raw[];
    if (threadIdx.x == 256) { map_prefetch(&maps.x); map_prefetch(&maps.wqkv); }
    const uint32_t sbw = __shfl_sync(0xffffffffu, ((smem_u32(smem_raw) + 1023u) & ~1023u) + (threadIdx.x >> 5), 0);
    const uint32_t sb = sbw & ~1023u;
    const int warp = sbw & 1023u;
    const int lane = threadIdx.x & 31;
    const int rank = blockIdx.x & 1;
    int mi, pr;
    {
        const int c = blockIdx.x >> 1;
        int g, m;
        if (c < 4) { g = 15; m = c; }
        else if (c < 36) { g = (c - 4) & 7; m = (c - 4) >> 3; }
        else { m = ((c - 36) * 37) >> 8; g = 8 + (c - 36) - 7 * m; }
        mi = (g & ~1) | (m & 1);
        pr = (g & 1) * 2 + (m >> 1);
    }
    const int j = pr * 2 + rank;
    const int row0 = mi * 128;
    if ((threadIdx.x >> 5) == 4) {
        const char* xp = args.x + (row0 + j * 8 + (lane >> 2)) * (D_ * 2) + (lane & 3) * 128;
        asm volatile("prefetch.global.L2 [%0];" ::"l"(xp) : "memory");
        asm volatile("prefetch.global.L2 [%0];" ::"l"(xp + 512) : "memory");
    }
    if (warp == 0) {
        if (elect_one()) {
            mbar_init(sb + B_XFULL, 1);
            mbar_expect_tx(sb + B_XFULL, 16384);
            fence_async_smem();
            tma3d(sb + SM_XA, &maps.x, 0, row0, 0, sb + B_XFULL);
#pragma unroll
            for (int i = 1; i < 8; ++i) mbar_init(sb + B_XFULL + i * 8, 1);
#pragma unroll
            for (int i = 0; i < NSTG; ++i) mbar_init(sb + B_FULL + i * 8, 1);
            fence_async_smem();
#pragma unroll
            for (int i = 1; i < 8; ++i) {
                mbar_expect_tx(sb + B_XFULL + i * 8, 16384);
                tma3d(sb + SM_XA + i * 16384, &maps.x, 0, row0 + (i >> 2) * 64, (i & 3) * 2, sb + B_XFULL + i * 8);
            }
        }
        __syncwarp();
        bar_arrive(3, 256);
        bar_arrive(4, 160);
    }
    const uint32_t swz = (lane & 15) * 128 + (((lane >> 4) ^ (lane & 7)) << 4);

    if (warp >= 8) {
        asm volatile("setmaxnreg.dec.sync.aligned.u32 40;");
        if (warp == 8) {
            asm volatile("barrier.cluster.arrive.relaxed.aligned;" ::: "memory");
            bar_sync(3, 256);
            if (elect_one()) {
#pragma unroll
                for (int i = 0; i < NSLOT; ++i) mbar_init(sb + B_EMPTY + i * 8, 8);
#pragma unroll
                for (int i = NSTG; i < NSLOT; ++i) mbar_init(sb + B_FULL + i * 8, 1);
                fence_async_smem();
            }
            __syncwarp();
#pragma unroll 1
            for (int g = 0; g < 40; ++g) {
                const int s = g & 3, c = g >> 2;
                const uint32_t slot = (uint32_t)((g < XSL ? SLOTS0 : SLOTS1) >> (4 * (g < XSL ? g : (g - XSL) & 7))) & 7;
                const uint32_t dst = sb + SM_RING + slot * STG_BYTES, bar = sb + B_FULL + slot * 8;
                const int jj = j ^ (s >> 1);
                const bool two = c >= 6 && (s & 1);
                const bool att = c < 2 || c == 3;
                const CUtensorMap* m = att ? &maps.wqkv : c < 6 ? &maps.w1 : two ? &maps.wo : &maps.w2;
                const int col = att ? 64 * j + (c == 3 ? 0 : 512 * (c + 1)) : c < 6 ? 176 * j + (c == 2 ? 0 : 64 * (c - 3)) : 256 * rank + 64 * (c - 6);
                const int row = c < 6 ? s * 128 : (two ? 64 : 176) * jj;
                if (g == XSL) asm volatile("barrier.cluster.wait.aligned;" ::: "memory");
                if ((REUSE >> g) & 1) mbar_wait(bar + (B_EMPTY - B_FULL), (uint32_t)(~PARS >> g) & 1);
                if (elect_one()) {
                    mbar_expect_tx(bar, two ? 112 * 128 : STG_BYTES);
                    tma2d(dst, m, col, row, bar);
                    if (two) tma2d(dst + 8192, &maps.w2b, col, 176 * jj + 128, bar);
                }
            }
            __syncwarp();
            mbar_wait(sb + B_DONE, 0);
        } else if (warp == 11) {
            bar_sync(3, 256);
            const unsigned epoch = *(volatile unsigned*)&g_count >> 7;
#pragma unroll
            for (int f = 0; f < 3; ++f) {
                const int col = 64 * f + 2 * lane;
                uint32_t v = 0;
                if (col < 176 && 176 * j + col < F_) v = __ldg((const uint32_t*)(args.b1 + 176 * j + col));
                const float lo = __uint_as_float(v << 16) * LOG2E, hi = __uint_as_float(v & 0xffff0000u) * LOG2E;
                asm volatile("st.shared.v2.f32 [%0], {%1,%2};" ::"r"(sb + SM_BIAS + f * 256 + (lane >> 3) * 64 + (lane & 3) * 16 + (lane & 4) * 2), "f"(lo), "f"(hi) : "memory");
            }
            if (lane == 0) asm volatile("st.shared.u64 [%0], %1;" ::"r"(sb + SM_KVOFF), "l"(&g_kv[epoch & 1][j][0]) : "memory");
            if (lane < 24) *(float4*)&g_kv[(epoch & 1) ^ 1][j][mi * 96 + lane * 4] = make_float4(0.f, 0.f, 0.f, 0.f);
            mbar_wait(sb + B_FULL, 0);
            if (elect_one()) {
                l2_prefetch(args.w[0] + blockIdx.x * (3 * D_ * D_ * 2 / NCTA), 3 * D_ * D_ * 2 / NCTA);
                l2_prefetch(args.w[1] + blockIdx.x * (F_ * D_ * 2 / NCTA), F_ * D_ * 2 / NCTA);
                l2_prefetch(args.w[2] + blockIdx.x * (F_ * D_ * 2 / NCTA), F_ * D_ * 2 / NCTA);
                l2_prefetch(args.w[3] + blockIdx.x * (D_ * D_ * 2 / NCTA), D_ * D_ * 2 / NCTA);
                map_prefetch(&maps.w1); map_prefetch(&maps.w2); map_prefetch(&maps.w2b); map_prefetch(&maps.wo); map_prefetch(&maps.ored);
            }
            __syncwarp();
            asm volatile("barrier.cluster.arrive.release.aligned; barrier.cluster.wait.aligned;" ::: "memory");
        } else {
            const int hw = warp - 9;
            bar_sync(3, 256);
            if (lane == 0) {
                if (hw == 0) {
#pragma unroll
                    for (int i = 0; i < 8; ++i) { mbar_init(sb + B_PF + i * 8, 1); mbar_init(sb + B_PO + i * 8, 1); }
#pragma unroll
                    for (int i = 0; i < 8; ++i) { mbar_expect_tx(sb + B_PF + i * 8, 4096); mbar_expect_tx(sb + B_PO + i * 8, 3584); }
                } else {
                    mbar_init(sb + B_KVST, 8);
                    mbar_init(sb + B_KVRDY, 2);
                    mbar_init(sb + B_OINIT, 1);
                    mbar_init(sb + B_DONE, 8);
                }
                asm volatile("fence.mbarrier_init.release.cluster;" ::: "memory");
            }
            __syncwarp();
            mbar_wait(sb + B_FULL, 0);
            const unsigned epoch = *(volatile unsigned*)&g_count >> 7;
            if (hw == 0 && elect_one()) {
                mbar_wait(sb + B_XFULL + (j >> 1) * 8, 0);
                tma_store2d(&maps.oinit, 64 * j, row0, sb + SM_XA + j * 8192);
                mbar_wait(sb + B_XFULL + (4 + (j >> 1)) * 8, 0);
                tma_store2d(&maps.oinit, 64 * j, row0 + 64, sb + SM_XA + 65536 + j * 8192);
                asm volatile("cp.async.bulk.commit_group; cp.async.bulk.wait_group.read 0;" ::: "memory");
            }
            __syncwarp();
            asm volatile("barrier.cluster.arrive.relaxed.aligned; barrier.cluster.wait.aligned;" ::: "memory");
            if (elect_one()) {
                if (hw == 0) {
                    asm volatile("cp.async.bulk.wait_group 0;" ::: "memory");
                    fence_async_all();
                    mbar_wait(sb + B_KVST, 0);
                    asm volatile("fence.acq_rel.gpu; red.relaxed.gpu.global.add.u32 [%0], 1;" ::"l"(&g_count) : "memory");
                } else {
                    mbar_wait(sb + B_KVST, 0);
                }
                const unsigned target = (epoch + 1) << 7;
                for (int it = 0;; ++it) {
                    unsigned v;
                    asm volatile("ld.acquire.gpu.global.u32 %0, [%1];" : "=r"(v) : "l"(&g_count) : "memory");
                    if ((int)(v - target) >= 0) break;
                    if (it > SPIN_LIMIT) asm volatile("trap;");
                }
            }
            __syncwarp();
            const float* gk = &g_kv[epoch & 1][j][hw * 2 * KV_HEAD];
#pragma unroll
            for (int h = 0; h < 2; ++h) {
                const float4 t0 = __ldcg((const float4*)(gk + h * KV_HEAD + lane * 4));
                const float4 t1 = __ldcg((const float4*)(gk + h * KV_HEAD + 128 + lane * 4));
                const float z = __ldcg(gk + h * KV_HEAD + 256 + (lane & 7) * 16 + ((lane >> 3) & 1) * 2);
                const uint32_t base = sb + X_KVB + hw * 2048;
                stsm4(base + (swz ^ (h << 6)), pack2(t0.x, t0.y), pack2(t0.z, t0.w), pack2(t1.x, t1.y), pack2(t1.z, t1.w));
                const uint32_t zz = pack2(z, z);
                if (lane < 16) sts4(base + lane * 128 + (((h * 4 + 2) ^ (lane & 7)) << 4), zz, zz, zz, zz);
            }
            fence_async_smem();
            __syncwarp();
            if (lane == 0) mbar_arrive(sb + B_KVRDY);
            if (hw == 0) {
                fence_async_all();
                __syncwarp();
                if (lane == 0) mbar_arrive(sb + B_OINIT);
            }
        }
    } else {
        asm volatile("setmaxnreg.inc.sync.aligned.u32 232;");
        asm volatile(".reg .pred pfull, paux, plane0, preal; setp.eq.u32 plane0, %0, 0;" ::"r"(lane));
        const int g = warp >> 2, wl = warp & 3;
        uint32_t A[128];
        float d[32];
        uint64_t db;
        const uint32_t tile = sb + X_PQ + g * 24576 + wl * 2048;
        const uint32_t bias = sb + SM_BIAS + (lane & 3) * 16;
        const uint32_t peer = mapa(sb, rank ^ 1);
        const int nw = 2 - g;
#pragma unroll 1
        for (int pass = 1 - g; pass < 2; ++pass) {
            asm volatile("setp.ne.u32 preal, %0, 0;" ::"r"(pass));
            if (pass && warp) bar_sync(3 + g, 256 - 96 * g);
            float st[4][4];
#pragma unroll
            for (int i = 0; i < 4; ++i)
#pragma unroll
                for (int k = 0; k < 4; ++k) st[i][k] = 0.f;
            const uint32_t xb = sb + SM_XA + g * 65536 + wl * 2048;
            const uint32_t lsw = ((lane & 7) + (lane >> 4) * 8) * 128 + ((((lane >> 3) & 1) ^ (lane & 7)) << 4);
            const uint32_t xf = sb + B_XFULL + g * 32;
#pragma unroll
            for (int e = 0; e < 4; ++e) {
                if (e == 0) asm volatile("{.reg .pred p; .reg .u32 it;\n@!preal bra DONE;\n" WAIT_LOOP ::"r"(xf), "r"(0), "n"(SPIN_LIMIT) : "memory");
                else asm volatile("{.reg .pred p; .reg .u32 it;\n@pfull bra DONE;\n@!preal bra DONE;\n" WAIT_LOOP ::"r"(xf + e * 8), "r"(0), "n"(SPIN_LIMIT) : "memory");
#pragma unroll
                for (int t = 0; t < 8; ++t) {
                    const int s = e * 8 + t;
                    ldsm4(A[4 * s], A[4 * s + 1], A[4 * s + 2], A[4 * s + 3], xb + (s >> 2) * 8192 + (lsw ^ ((s & 3) << 5)));
                }
                if (e < 3) mbar_test(xf + e * 8 + 8, 0);
#pragma unroll
                for (int s = 0; s < 32; ++s)
                    if (s >= e * 8 - XDEF && (s < e * 8 + 8 - XDEF || e == 3)) {
                        mma16816(st[(s & 1) * 2], A[4 * s], ONES2, A[4 * s + 1], ONES2, A[4 * s], A[4 * s + 1]);
                        mma16816(st[(s & 1) * 2 + 1], A[4 * s + 2], ONES2, A[4 * s + 3], ONES2, A[4 * s + 2], A[4 * s + 3]);
                    }
            }
            asm volatile("@preal barrier.cluster.arrive.relaxed.aligned;" ::: "memory");
            if (!pass) continue;
            if (g) {
                bar_sync(1, 256);
                mbar_wait(sb + B_XFULL, 0);
            }
            const int r = lane >> 2;
            const int src = 4 * r + (r >> 1);
            const bool odd = r & 1;
            const float q0 = __shfl_sync(0xffffffffu, odd ? st[0][1] + st[2][1] : st[0][0] + st[2][0], src);
            const float s0 = __shfl_sync(0xffffffffu, odd ? st[0][3] + st[2][3] : st[0][2] + st[2][2], src);
            const float q1 = __shfl_sync(0xffffffffu, odd ? st[1][1] + st[3][1] : st[1][0] + st[3][0], src);
            const float s1 = __shfl_sync(0xffffffffu, odd ? st[1][3] + st[3][3] : st[1][2] + st[3][2], src);
            const float m0 = s0 * (1.f / D_), m1 = s1 * (1.f / D_);
            const uint32_t rr = pack2(LOG2E * rsqf(fmaxf(fmaf(q0, 1.f / D_, -m0 * m0), 0.f) + 1e-5f), LOG2E * rsqf(fmaxf(fmaf(q1, 1.f / D_, -m1 * m1), 0.f) + 1e-5f));
            const float c0 = -m0 * __uint_as_float(rr << 16), c1 = -m1 * __uint_as_float(rr & 0xffff0000u);
            const uint32_t r0 = __byte_perm(rr, 0, 0x1010), r1 = __byte_perm(rr, 0, 0x3232), cc0 = pack2(c0, c0), cc1 = pack2(c1, c1);
#pragma unroll
            for (int s = 0; s < 32; ++s)
                asm volatile("{.reg .b32 t;\n"
                             "fma.rn.bf16x2 t, %1, %4, %5;\n"
                             "fma.rn.bf16x2 %0, %0, %4, %5;\n"
                             "fma.rn.bf16x2 %1, %2, %6, %7;\n"
                             "fma.rn.bf16x2 %3, %3, %6, %7;\n"
                             "prmt.b32 %2, t, t, %8;}"
                             : "+r"(A[4 * s]), "+r"(A[4 * s + 1]), "+r"(A[4 * s + 2]), "+r"(A[4 * s + 3]) : "r"(r0), "r"(cc0), "r"(r1), "r"(cc1), "r"(args.ident));
        }
        mbar_wait(sb + full_bar(0), 0);
        chunk_begin<0>(args, db, sb, g);
        g1_mma<64, 0, true>(d, A, sb, db, nw);
        chunk_end<3>(sb);
        const uint32_t pk = sb + X_KV + g * 65536 + (j == 5 ? 8192 : 0), vt = sb + X_KV + g * 65536 + (j == 5 ? 0 : 8192);
        phi_tile(d, pk + wl * 2048 + swz);
        chunk_begin<4>(args, db, sb, g);
        g1_mma<64, 1, true>(d, A, sb, db, nw);
        chunk_end<7>(sb);
        asm volatile("barrier.cluster.wait.aligned;" ::: "memory");
#pragma unroll
        for (int u = 0; u < 4; ++u) {
            stsm4((vt + wl * 2048 + swz) ^ (u << 5), pack2(d[8 * u], d[8 * u + 1]), pack2(d[8 * u + 2], d[8 * u + 3]), pack2(d[8 * u + 4], d[8 * u + 5]), pack2(d[8 * u + 6], d[8 * u + 7]));
            load_bias16(&d[8 * u], bias + u * 64, args.ident);
        }
        sts4(sb + X_KVB + wl * 512 + lane * 16, ONES2, ONES2, ONES2, ONES2);
        fence_async_smem();
        {
            float kv[36];
            const uint32_t pk_lo = desc_lo(pk);
            const uint32_t v_lo = desc_lo(vt) + ((sb + X_KVB - vt) << 12);
            const char* gk;
            asm volatile("ld.shared.u64 %0, [%1];" : "=l"(gk) : "r"(sb + SM_KVOFF) : "memory");
            gk += wl * (KV_HEAD * 4) + lane * 16;
            chunk_begin<8>(args, db, sb, g);
            wgmma_ss72t<false>(kv, pk_lo, v_lo);
#pragma unroll
            for (int k = 1; k < 4; ++k) wgmma_ss72t<true>(kv, pk_lo + k * 128, v_lo + k * (128 - (128 << 16)));
            mma_stage<64, 8, 0, 8, 0, false>(d, A, sb, db, nw);
            mma_stage<64, 9, 8, 8, 1, false>(d, A, sb, db, nw);
            mma_stage<64, 10, 16, 8, 1, false>(d, A, sb, db, nw, [&](int k) {
                if (k >= 0 && k < 4) red8_if(wl, k, gk, &kv[8 * (k & 3)]);
                if (k == 4) red4_if(lane & 3, 0, gk, &kv[32]);
                if (k == 5) { __syncwarp(); mbar_arrive_lane0(sb + B_KVST); }
            });
            mma_stage<64, 11, 24, 8, 2, false>(d, A, sb, db, nw);
            chunk_end<11>(sb);
        }
        uint32_t G[128];
#pragma unroll
        for (int u = 0; u < 8; ++u) mish4(&d[4 * u], &G[2 * u]);
#pragma unroll
        for (int i = 0; i < 16; ++i) asm volatile("" : "+r"(G[i]));
        const uint32_t pf = peer + X_PF + warp * 4096 + lane * 16, plo = X_KV + g * 65536 + wl * 3584 + lane * 16, pl = peer + plo;
        const uint32_t lf = sb + X_PF + warp * 4096 + lane * 16, ll = sb + plo;
        auto send = [&](int q) { st_async4(pf + q * 512, &G[4 * q], peer + B_PF + warp * 8); };
        chunk_begin<12>(args, db, sb, g);
        mma_stage<64, 12, 0, 8, 0, true>(d, A, sb, db, nw, [&](int k) {
            if (k == 1 || k == 5) send(k >> 2);
            if (k == 3) sts4(sb + X_OWN + warp * 512 + lane * 16, G[0], G[1], G[2], G[3]);
        });
        mma_stage<64, 13, 8, 8, 1, false>(d, A, sb, db, nw, [&](int k) { if (k == 1 || k == 5) send(2 + (k >> 2)); });
        mma_stage<64, 14, 16, 8, 1, false>(d, A, sb, db, nw);
        mma_stage<64, 15, 24, 8, 2, false>(d, A, sb, db, nw);
        chunk_end<15>(sb);
#pragma unroll
        for (int u = 0; u < 4; ++u) {
            const uint32_t p0 = phi2(d[8 * u], d[8 * u + 1]), p1 = phi2(d[8 * u + 2], d[8 * u + 3]), p2 = phi2(d[8 * u + 4], d[8 * u + 5]), p3 = phi2(d[8 * u + 6], d[8 * u + 7]);
            load_bias16(&d[8 * u], bias + 256 + u * 64, args.ident);
            stsm4((tile + swz) ^ (u << 5), p0, p1, p2, p3);
        }
        chunk_begin<16>(args, db, sb, g);
        mma_stage<64, 16, 0, 8, 0, false>(d, A, sb, db, nw);
        mma_stage<64, 17, 8, 8, 1, false>(d, A, sb, db, nw);
        mma_stage<64, 18, 16, 8, 1, false>(d, A, sb, db, nw, [&](int k) { if (k == 1) fence_async_smem(); });
        mma_stage<64, 19, 24, 8, 2, false>(d, A, sb, db, nw);
        chunk_end<19>(sb);
#pragma unroll
        for (int u = 0; u < 4; ++u) {
            mish4(&d[8 * u], &G[16 + 4 * u]);
            mish4(&d[8 * u + 4], &G[18 + 4 * u]);
            if (u < 3) load_bias16(&d[8 * u], bias + 512 + u * 64, args.ident);
        }
#pragma unroll
        for (int i = 16; i < 32; ++i) asm volatile("" : "+r"(G[i]));
        {
            float o[2][12];
            const uint32_t pq_lo = desc_lo(sb + X_PQ + g * 24576) | (1u << 16);
            const uint32_t kv_lo = desc_lo(sb + X_KVB) | (1u << 16);
            chunk_begin<20>(args, db, sb, g);
            mma_stage<48, 20, 0, 8, 0, false>(d, A, sb, db, nw, [&](int k) { if (k == 1 || k == 5) send(4 + (k >> 2)); });
            mma_stage<48, 21, 8, 8, 1, false>(d, A, sb, db, nw, [&](int k) { if (k == 1 || k == 5) send(6 + (k >> 2)); });
            mma_stage<48, 22, 16, 8, 1, false>(d, A, sb, db, nw);
            mma_stage<48, 23, 24, 8, 2, false>(d, A, sb, db, nw);
            chunk_end<23>(sb);
            lds4(&G[0], sb + X_OWN + warp * 512 + lane * 16);
            mbar_wait(sb + B_KVRDY, 0);
#pragma unroll
            for (int p = 0; p < 2; ++p) {
                wg_fence();
                wgmma_ss24(o[0], pq_lo + 4 * p, kv_lo + 128 * p);
                wgmma_ss24(o[1], pq_lo + 4 * p + 2, kv_lo + 128 * p + 4);
                wg_commit();
#pragma unroll
                for (int u = 3 * p; u < 3 * p + 3; ++u) {
                    mish4(&d[4 * u], &G[48 + 2 * u]);
                    if (u & 1) st_async4(pl + 2048 + (u >> 1) * 512, &G[46 + 2 * u], peer + B_PO + warp * 8);
                }
                wg_wait<0>();
                if (p == 1) aux_test(sb + B_PF + warp * 8);
#pragma unroll
                for (int h = 0; h < 2; ++h) {
                    const float i0 = rcpf(o[h][8] + 1e-6f), i1 = rcpf(o[h][10] + 1e-6f);
                    uint32_t* a = &G[32 + 8 * p + 4 * h];
                    a[0] = pack2(o[h][0] * i0, o[h][1] * i0);
                    a[1] = pack2(o[h][2] * i1, o[h][3] * i1);
                    a[2] = pack2(o[h][4] * i0, o[h][5] * i0);
                    a[3] = pack2(o[h][6] * i1, o[h][7] * i1);
                    st_async4(pl + (2 * p + h) * 512, a, peer + B_PO + warp * 8);
                }
            }
        }
        auto g2_store = [&](int c) {
            const uint32_t stg = sb + X_PF + warp * 4096 + (c & 1) * 2048;
            if (c >= 2) {
                asm volatile("cp.async.bulk.wait_group.read 1;" ::: "memory");
                __syncwarp();
            }
#pragma unroll
            for (int u = 0; u < 4; ++u)
                stsm4((stg + swz) ^ (u << 5), pack2(d[8 * u] * LN2, d[8 * u + 1] * LN2), pack2(d[8 * u + 2] * LN2, d[8 * u + 3] * LN2),
                      pack2(d[8 * u + 4] * LN2, d[8 * u + 5] * LN2), pack2(d[8 * u + 6] * LN2, d[8 * u + 7] * LN2));
            if (c == 3) {
                __syncwarp();
                char* p = args.out + (row0 + warp * 16 + (lane >> 3)) * (D_ * 2) + 512 * rank + 384 + (lane & 7) * 16;
#pragma unroll
                for (int u = 0; u < 4; ++u) {
                    uint32_t v[4];
                    lds4(v, stg + (4 * u + (lane >> 3)) * 128 + (((lane & 7) ^ ((4 * u + (lane >> 3)) & 7)) << 4));
                    asm volatile("red.relaxed.gpu.global.add.noftz.v4.bf16x2 [%0], {%1,%2,%3,%4};"
                                 ::"l"(p + u * 4 * D_ * 2), "r"(v[0]), "r"(v[1]), "r"(v[2]), "r"(v[3]) : "memory");
                }
                return;
            }
            fence_async_smem();
            __syncwarp();
            if (c == 0) mbar_wait(sb + B_OINIT, 0);
            if (elect_one()) {
                tma_red2d(&maps.ored, 256 * rank + 64 * c, row0 + warp * 16, stg);
                asm volatile("cp.async.bulk.commit_group;" ::: "memory");
            }
        };
        auto fetch = [&](int first, int n, uint32_t addr) {
#pragma unroll
            for (int s = 0; s < n; ++s) lds4(&G[4 * (first + s)], addr + s * 512);
        };
        aux_check(sb + B_PF + warp * 8);
        chunk_begin<24>(args, db, sb, g);
        mma_stage<64, 24, 0, 8, 0, true>(d, G, sb, db, nw, [&](int k) {
            if (k == 1) fetch(15, 4, lf);
        });
        mma_stage<64, 25, 8, 7, 1, false>(d, G, sb, db, nw, [&](int k) {
            if (k == -1) fetch(19, 4, lf + 2048);
            if (k == 5) aux_test(sb + B_PO + warp * 8);
        });
        aux_check(sb + B_PO + warp * 8);
        mma_stage<64, 26, 15, 8, 1, false>(d, G, sb, db, nw, [&](int k) {
            if (k == -1) { wg_fence(); fetch(23, 4, ll); }
            if (k == 2) fetch(27, 3, ll + 2048);
            if (k == 6) asm volatile("@plane0 mbarrier.arrive.shared::cluster.b64 _, [%0];" ::"r"(peer + B_DONE) : "memory");
        });
        wg_fence();
        mma_stage<64, 27, 23, 7, 2, false>(d, G, sb, db, nw);
        chunk_end<27>(sb);
        g2_store(0);
#define G2_CHUNK(C, NEXT) \
        chunk_begin<24 + 4 * C>(args, db, sb, g); \
        mma_stage<64, 24 + 4 * C, 0, 8, 0, true>(d, G, sb, db, NEXT); \
        mma_stage<64, 25 + 4 * C, 8, 7, 1, false>(d, G, sb, db, NEXT); \
        mma_stage<64, 26 + 4 * C, 15, 8, 1, false>(d, G, sb, db, NEXT); \
        mma_stage<64, 27 + 4 * C, 23, 7, 2, false>(d, G, sb, db, NEXT); \
        chunk_end<27 + 4 * C>(sb); \
        g2_store(C);
        G2_CHUNK(1, nw)
        G2_CHUNK(2, nw)
        G2_CHUNK(3, nw & 2)
        asm volatile("cp.async.bulk.wait_group.read 0;" ::: "memory");
    }
}

typedef CUresult (*EncodeFn)(CUtensorMap*, CUtensorMapDataType, cuuint32_t, void*, const cuuint64_t*, const cuuint64_t*, const cuuint32_t*, const cuuint32_t*,
                             CUtensorMapInterleave, CUtensorMapSwizzle, CUtensorMapL2promotion, CUtensorMapFloatOOBfill);

void make_map(EncodeFn enc, CUtensorMap* m, const void* base, int rank, const cuuint64_t* dims, const cuuint64_t* strides, const cuuint32_t* box) {
    const cuuint32_t es[3] = {1, 1, 1};
    enc(m, CU_TENSOR_MAP_DATA_TYPE_BFLOAT16, rank, const_cast<void*>(base), dims, strides, box, es, CU_TENSOR_MAP_INTERLEAVE_NONE,
        CU_TENSOR_MAP_SWIZZLE_128B, CU_TENSOR_MAP_L2_PROMOTION_L2_128B, CU_TENSOR_MAP_FLOAT_OOB_FILL_NONE);
}
void make_map2(EncodeFn enc, CUtensorMap* m, const void* base, int cols, int rows, int box_rows) {
    const cuuint64_t dims[2] = {(cuuint64_t)cols, (cuuint64_t)rows};
    const cuuint64_t strides[1] = {(cuuint64_t)cols * 2};
    const cuuint32_t box[2] = {64, (cuuint32_t)box_rows};
    make_map(enc, m, base, 2, dims, strides, box);
}

}

extern "C" void kernel_launch(void* const* d_in, const int* in_sizes, int n_in, void* d_out, int out_size) {
    (void)in_sizes; (void)n_in; (void)out_size;
    static EncodeFn enc = nullptr;
    if (!enc) {
        void* p = nullptr;
        cudaDriverEntryPointQueryResult qr;
        cudaGetDriverEntryPoint("cuTensorMapEncodeTiled", &p, cudaEnableDefault, &qr);
        enc = (EncodeFn)p;
        cudaFuncSetAttribute(fused_kernel, cudaFuncAttributeMaxDynamicSharedMemorySize, SMEM_BYTES);
    }
    Maps maps;
    {
        const cuuint64_t dims[3] = {64, S_, D_ / 64};
        const cuuint64_t strides[2] = {D_ * 2, 128};
        const cuuint32_t box[3] = {64, 64, 2};
        make_map(enc, &maps.x, d_in[0], 3, dims, strides, box);
    }
    Args args;
    args.x = (const char*)d_in[0];
    for (int c = 0; c < 10; ++c) args.desc[c] = ((uint64_t)0x40000040u << 32) | (1u << 16) | (uint64_t)(slot_of(4 * c) * (STG_BYTES >> 4));
    args.ident = 0x3210;
    args.out = (char*)d_out;
    args.b1 = (const __nv_bfloat16*)d_in[5];
    args.w[0] = (const char*)d_in[1]; args.w[1] = (const char*)d_in[4]; args.w[2] = (const char*)d_in[6]; args.w[3] = (const char*)d_in[2];
    make_map2(enc, &maps.wqkv, d_in[1], 3 * D_, D_, 128);
    make_map2(enc, &maps.w1, d_in[4], F_, D_, 128);
    make_map2(enc, &maps.w2, d_in[6], D_, F_, 128);
    make_map2(enc, &maps.w2b, d_in[6], D_, F_, 48);
    make_map2(enc, &maps.wo, d_in[2], D_, D_, 64);
    make_map2(enc, &maps.oinit, d_out, D_, S_, 64);
    make_map2(enc, &maps.ored, d_out, D_, S_, 16);
    fused_kernel<<<NCTA, 384, SMEM_BYTES, cudaStreamPerThread>>>(args, maps);
}
```
